```python
import torch

def _softmax(x, axis=-1):
    return torch.softmax(x, dim=axis)
def _gelu(x):
    return torch.nn.functional.gelu(x, approximate="tanh")
def _silu(x):
    return torch.nn.functional.silu(x)
def _sigmoid(x):
    return torch.sigmoid(x)
def _layernorm(x, axis=-1, eps=1e-5):
    m = x.mean(dim=axis, keepdim=True)
    v = x.var(dim=axis, keepdim=True, unbiased=False)
    return (x - m) / torch.sqrt(v + eps)
def _scatter_add(tgt, idx, src, axis=0):
    return tgt.clone().index_add_(axis, idx, src)
def _segment_sum(src, seg, n):
    out = torch.zeros((n,) + src.shape[1:], dtype=src.dtype)
    return out.index_add_(0, seg, src)
def _pad(x, pw):
    flat = tuple(v for pair in reversed(pw) for v in pair)
    return torch.nn.functional.pad(x, flat)

kernel_name = 'standalone__gqa_softmax__sampling'

def setup_inputs():

    _w = (lambda a: (lambda t: t.to(torch.bfloat16) if t.is_floating_point() else t)(torch.as_tensor(a)))
    B, Hq, Hkv, Sq, Sk, D = 8, 32, 8, 4, 8192, 128
    return {
        "q": _w((lambda *s: torch.randn(*s, dtype=torch.bfloat16) * 0.8)(B, Hq, Sq, D)),
        "k": _w((lambda *s: torch.randn(*s, dtype=torch.bfloat16) * 0.8)(B, Hkv, Sk, D)),
        "v": _w((lambda *s: torch.randn(*s, dtype=torch.bfloat16) * 0.05)(B, Hkv, Sk, D)),
    }

def reference(q, k, v):
    B, Hq, Sq, D = q.shape
    Hkv = k.shape[1]
    rep = Hq // Hkv
    k = (lambda x, n, axis: torch.repeat_interleave(x, n, dim=axis))(k, rep, axis=1)
    v = (lambda x, n, axis: torch.repeat_interleave(x, n, dim=axis))(v, rep, axis=1)
    scale = D ** -0.5
    scores = torch.einsum("bhqd,bhkd->bhqk", q, k) * scale
    p = _softmax(scores, axis=-1)
    return torch.einsum("bhqk,bhkd->bhqd", p, v)
```

```cpp
#include <cuda_runtime.h>
#include <cuda_bf16.h>
#include <cuda.h>
#include <stdint.h>

namespace {

constexpr int kD = 128;
constexpr int kSk = 8192;
constexpr int kHeads = 64;
constexpr int kQRows = 16;
constexpr int kTile = 128;
constexpr int kTilesPerCta = kSk / 2 / kTile;
constexpr int kLoads = 2 * kTilesPerCta;
constexpr int kSlots = 6;
constexpr uint32_t kTileBytes = kTile * kD * 2;
constexpr uint32_t kQBytes = kQRows * kD * 2;
constexpr uint32_t kPBytes = kTile * kQRows * 2;

constexpr uint32_t kOffRing = 0;
constexpr uint32_t kOffQ = kOffRing + kSlots * kTileBytes;
constexpr uint32_t kOffP = kOffQ + kQBytes;
constexpr uint32_t kOffXO = kOffP + 2 * kPBytes;
constexpr uint32_t kOffXS = kOffXO + 4096;
constexpr uint32_t kOffRed = kOffXS + 128;
constexpr uint32_t kOffBar = kOffRed + 512;
constexpr uint32_t kBarFull = kOffBar;
constexpr uint32_t kBarEmpty = kBarFull + 8 * kSlots;
constexpr uint32_t kBarXS = kBarEmpty + 8 * kSlots;
constexpr uint32_t kBarXO = kBarXS + 8;
constexpr uint32_t kSmemUsed = kBarXO + 8;
constexpr uint32_t kSmemBytes = kSmemUsed + 1024;

constexpr uint64_t kEvictFirst = 0x12F0000000000000ull;
constexpr int kSpinLimit = 1 << 24;

__device__ __forceinline__ void mbar_init(uint32_t bar, uint32_t count) {
    asm volatile("mbarrier.init.shared::cta.b64 [%0], %1;" ::"r"(bar), "r"(count) : "memory");
}
__device__ __forceinline__ void mbar_expect_tx(uint32_t bar, uint32_t bytes) {
    asm volatile("mbarrier.arrive.expect_tx.shared::cta.b64 _, [%0], %1;" ::"r"(bar), "r"(bytes) : "memory");
}
__device__ __forceinline__ void mbar_arrive(uint32_t bar) {
    asm volatile("mbarrier.arrive.shared::cta.b64 _, [%0];" ::"r"(bar) : "memory");
}
__device__ __forceinline__ void mbar_wait(uint32_t bar, uint32_t parity) {
    uint32_t ok;
    int spins = 0;
    do {
        asm volatile(
            "{ .reg .pred p; mbarrier.try_wait.parity.shared::cta.b64 p, [%1], %2; selp.u32 %0, 1, 0, p; }"
            : "=r"(ok) : "r"(bar), "r"(parity) : "memory");
        if (++spins > kSpinLimit) __trap();
    } while (!ok);
}
__device__ __forceinline__ void mbar_wait_cluster(uint32_t bar, uint32_t parity) {
    uint32_t ok;
    int spins = 0;
    do {
        asm volatile(
            "{ .reg .pred p; mbarrier.try_wait.parity.acquire.cluster.shared::cta.b64 p, [%1], %2; selp.u32 %0, 1, 0, p; }"
            : "=r"(ok) : "r"(bar), "r"(parity) : "memory");
        if (++spins > kSpinLimit) __trap();
    } while (!ok);
}
__device__ __forceinline__ void tma_load(uint32_t dst, const CUtensorMap* map, int group, uint32_t bar) {
    asm volatile(
        "cp.async.bulk.tensor.4d.shared::cluster.global.mbarrier::complete_tx::bytes.L2::cache_hint "
        "[%0], [%1, {%3, %3, %3, %4}], [%2], %5;"
        ::"r"(dst), "l"(map), "r"(bar), "r"(0), "r"(group), "l"(kEvictFirst) : "memory");
}
__device__ __forceinline__ void st_async_v4(uint32_t dst, float a, float b, float c, float d, uint32_t bar) {
    asm volatile("st.async.weak.shared::cluster.mbarrier::complete_tx::bytes.v4.f32 [%0], {%1, %2, %3, %4}, [%5];"
                 ::"r"(dst), "f"(a), "f"(b), "f"(c), "f"(d), "r"(bar) : "memory");
}
__device__ __forceinline__ float4 lds128(uint32_t addr) {
    float4 v;
    asm volatile("ld.shared.v4.f32 {%0, %1, %2, %3}, [%4];" : "=f"(v.x), "=f"(v.y), "=f"(v.z), "=f"(v.w) : "r"(addr) : "memory");
    return v;
}
__device__ __forceinline__ void sts32(uint32_t addr, float v) {
    asm volatile("st.shared.f32 [%0], %1;" ::"r"(addr), "f"(v) : "memory");
}
__device__ __forceinline__ void consumer_bar() { asm volatile("bar.sync 1, 128;" ::: "memory"); }
__device__ __forceinline__ float ex2(float x) {
    float y;
    asm("ex2.approx.ftz.f32 %0, %1;" : "=f"(y) : "f"(x));
    return y;
}
__device__ __forceinline__ uint32_t pack_bf16(float lo, float hi) {
    uint32_t r;
    asm("cvt.rn.bf16x2.f32 %0, %1, %2;" : "=r"(r) : "f"(hi), "f"(lo));
    return r;
}

__device__ __forceinline__ void wg_fence() { asm volatile("wgmma.fence.sync.aligned;" ::: "memory"); }
__device__ __forceinline__ void wg_commit() { asm volatile("wgmma.commit_group.sync.aligned;" ::: "memory"); }
__device__ __forceinline__ void wg_wait0() { asm volatile("wgmma.wait_group.sync.aligned 0;" ::: "memory"); }

template <int kAccumulate, int kTransA>
__device__ __forceinline__ void wgmma_m64n16k16(float (&d)[8], uint64_t a, uint64_t b) {
    asm volatile(
        "wgmma.mma_async.sync.aligned.m64n16k16.f32.bf16.bf16 "
        "{%0, %1, %2, %3, %4, %5, %6, %7}, %8, %9, %10, 1, 1, %11, 0;"
        : "+f"(d[0]), "+f"(d[1]), "+f"(d[2]), "+f"(d[3]), "+f"(d[4]), "+f"(d[5]), "+f"(d[6]), "+f"(d[7])
        : "l"(a), "l"(b), "n"(kAccumulate), "n"(kTransA));
}
__device__ __forceinline__ void pin(float (&d)[8]) {
    asm volatile("" : "+f"(d[0]), "+f"(d[1]), "+f"(d[2]), "+f"(d[3]), "+f"(d[4]), "+f"(d[5]), "+f"(d[6]), "+f"(d[7])::"memory");
}

__device__ __forceinline__ uint64_t desc_sw128(uint32_t addr) {
    return (uint64_t)((addr & 0x3FFFF) >> 4) | (1ull << 16) | ((uint64_t)(2048 >> 4) << 32) | (1ull << 62);
}
__device__ __forceinline__ uint64_t desc_p(uint32_t addr) {
    return (uint64_t)((addr & 0x3FFFF) >> 4) | ((uint64_t)(128 >> 4) << 16) | ((uint64_t)(256 >> 4) << 32);
}

template <bool kMax>
__device__ __forceinline__ float warp_col_reduce(const float (&x)[4], int lane) {
    const bool b2 = lane & 4, b3 = lane & 8;
    float a = b2 ? x[2] : x[0], b = b2 ? x[3] : x[1];
    const float sa = b2 ? x[0] : x[2], sb = b2 ? x[1] : x[3];
    const float ra = __shfl_xor_sync(0xffffffffu, sa, 4), rb = __shfl_xor_sync(0xffffffffu, sb, 4);
    a = kMax ? fmaxf(a, ra) : a + ra;
    b = kMax ? fmaxf(b, rb) : b + rb;
    float keep = b3 ? b : a;
    const float r2 = __shfl_xor_sync(0xffffffffu, b3 ? a : b, 8);
    keep = kMax ? fmaxf(keep, r2) : keep + r2;
    const float r3 = __shfl_xor_sync(0xffffffffu, keep, 16);
    return kMax ? fmaxf(keep, r3) : keep + r3;
}

__global__ void __cluster_dims__(2, 1, 1) __launch_bounds__(160, 1)
gqa_decode_kernel(const __grid_constant__ CUtensorMap map_k, const __grid_constant__ CUtensorMap map_v,
                  const __grid_constant__ CUtensorMap map_q, __nv_bfloat16* __restrict__ out) {
    extern __shared__ uint8_t smem_raw[];
    const uint32_t sb = ((uint32_t)__cvta_generic_to_shared(smem_raw) + 1023u) & ~1023u;
    const int tid = threadIdx.x;
    const int head = blockIdx.x >> 1;
    const int rank = blockIdx.x & 1;

    const int group0 = (head * kSk + rank * (kSk / 2)) / 8;
    constexpr int kGroupsPerTile = kTile / 8;

    if (tid == 128) {
#pragma unroll
        for (int i = 0; i < kSlots; i++) {
            const uint32_t bar = sb + kBarFull + 8 * i;
            mbar_init(bar, 1);
            mbar_expect_tx(bar, kTileBytes + (i == 0 ? kQBytes : 0));
            const bool is_v = i >= 2 && !(i & 1);
            const int tile = is_v ? (i - 2) / 2 : (i + 1) / 2;
            tma_load(sb + kOffRing + i * kTileBytes, is_v ? &map_v : &map_k, group0 + tile * kGroupsPerTile, bar);
            if (i == 0) tma_load(sb + kOffQ, &map_q, head * (kQRows / 8), bar);
        }
#pragma unroll
        for (int i = 0; i < kSlots; i++) mbar_init(sb + kBarEmpty + 8 * i, 4);
        mbar_init(sb + kBarXS, 1);
        mbar_init(sb + kBarXO, 1);
        mbar_expect_tx(sb + kBarXS, 128);
        mbar_expect_tx(sb + kBarXO, 4096);
        asm volatile("fence.mbarrier_init.release.cluster;" ::: "memory");
    }
    __syncthreads();
    asm volatile("barrier.cluster.arrive.release.aligned;" ::: "memory");

    if (tid >= 128) {
        if (tid == 128) {
            int slot = 0;
            uint32_t parity = 0;
            for (int i = kSlots; i < kLoads; i++) {
                const bool is_v = !(i & 1) || i == kLoads - 1;
                const int tile = i == kLoads - 1 ? kTilesPerCta - 1 : (is_v ? (i - 2) / 2 : (i + 1) / 2);
                const uint32_t bar = sb + kBarFull + 8 * slot;
                mbar_wait(sb + kBarEmpty + 8 * slot, parity);
                mbar_expect_tx(bar, kTileBytes);
                tma_load(sb + kOffRing + slot * kTileBytes, is_v ? &map_v : &map_k, group0 + tile * kGroupsPerTile, bar);
                if (++slot == kSlots) { slot = 0; parity ^= 1; }
            }
        }
        return;
    }

    const int lane = tid & 31, warp = tid >> 5;
    const int t4 = lane & 3;
    const int my_col = 2 * t4 + ((lane >> 3) & 1) + 8 * ((lane >> 2) & 1);
    const uint32_t red_wr = sb + kOffRed + (my_col * 4 + warp) * 4;
    const uint32_t red_rd = sb + kOffRed + (2 * t4) * 16;
    const float c = 0.08838834764831845f * 1.4426950408889634f;

    const uint64_t dq = desc_sw128(sb + kOffQ);
    float o[2][8], s[2][8];
    float m[4], l[4], alpha[4];
#pragma unroll
    for (int i = 0; i < 8; i++) o[0][i] = o[1][i] = 0.f;
#pragma unroll
    for (int j = 0; j < 4; j++) { m[j] = -INFINITY; l[j] = 0.f; }

    int slot = 0;
    uint32_t parity = 0;
    auto advance = [&]() { if (++slot == kSlots) { slot = 0; parity ^= 1; } };

    auto score_tile = [&](int tile) {
        mbar_wait(sb + kBarFull + 8 * slot, parity);
        const uint64_t dk = desc_sw128(sb + kOffRing + slot * kTileBytes);
        pin(s[0]); pin(s[1]);
        wg_fence();
#pragma unroll
        for (int k = 0; k < 8; k++) {
            const uint32_t off = ((k >> 2) * 1024 + (k & 3) * 32) >> 4;
#pragma unroll
            for (int mt = 0; mt < 2; mt++) {
                if (k == 0) wgmma_m64n16k16<0, 0>(s[mt], dk + off + mt * (16384 >> 4), dq + off);
                else        wgmma_m64n16k16<1, 0>(s[mt], dk + off + mt * (16384 >> 4), dq + off);
            }
        }
        wg_commit();
        wg_wait0();
        pin(s[0]); pin(s[1]);
        if (lane == 0) mbar_arrive(sb + kBarEmpty + 8 * slot);
        advance();

        float x[4];
#pragma unroll
        for (int j = 0; j < 4; j++) {
            const int i0 = (j >> 1) * 4 + (j & 1);
            x[j] = fmaxf(fmaxf(s[0][i0], s[0][i0 + 2]), fmaxf(s[1][i0], s[1][i0 + 2]));
        }
        const float wmax = warp_col_reduce<true>(x, lane);
        if (lane < 16) sts32(red_wr, wmax);
        consumer_bar();
        float mc[4];
#pragma unroll
        for (int j = 0; j < 4; j++) {
            const float4 r = lds128(red_rd + ((j >> 1) * 8 + (j & 1)) * 16);
            const float mn = fmaxf(fmaxf(fmaxf(r.x, r.y), fmaxf(r.z, r.w)), m[j]);
            alpha[j] = ex2((m[j] - mn) * c);
            m[j] = mn;
            mc[j] = mn * c;
            l[j] *= alpha[j];
        }
        const uint32_t p_wr = sb + kOffP + (tile & 1) * kPBytes + warp * 512 + lane * 16;
#pragma unroll
        for (int mt = 0; mt < 2; mt++) {
            float p[8];
#pragma unroll
            for (int i = 0; i < 8; i++) {
                const int j = (i >> 2) * 2 + (i & 1);
                p[i] = ex2(fmaf(s[mt][i], c, -mc[j]));
                l[j] += p[i];
            }
            asm volatile("stmatrix.sync.aligned.m8n8.x4.trans.shared.b16 [%0], {%1, %2, %3, %4};"
                         ::"r"(p_wr + mt * 2048), "r"(pack_bf16(p[0], p[1])), "r"(pack_bf16(p[2], p[3])),
                           "r"(pack_bf16(p[4], p[5])), "r"(pack_bf16(p[6], p[7])) : "memory");
        }
        asm volatile("fence.proxy.async.shared::cta;" ::: "memory");
        consumer_bar();
    };

    auto issue_pv = [&](int tile) {
        mbar_wait(sb + kBarFull + 8 * slot, parity);
        const uint64_t dv = desc_sw128(sb + kOffRing + slot * kTileBytes);
        const uint64_t dp = desc_p(sb + kOffP + (tile & 1) * kPBytes);
        pin(o[0]); pin(o[1]);
        wg_fence();
#pragma unroll
        for (int k = 0; k < 8; k++) {
#pragma unroll
            for (int h = 0; h < 2; h++)
                wgmma_m64n16k16<1, 1>(o[1 - h], dv + k * (4096 >> 4) + ((1 - h) ^ rank) * (1024 >> 4), dp + k * (512 >> 4));
        }
        wg_commit();
    };
    auto rescale = [&]() {
#pragma unroll
        for (int i = 0; i < 8; i++) {
            const int j = (i >> 2) * 2 + (i & 1);
            o[0][i] *= alpha[j];
            o[1][i] *= alpha[j];
        }
    };

    score_tile(0);
    for (int tile = 0; tile < kTilesPerCta - 1; tile++) {
        score_tile(tile + 1);
        issue_pv(tile);
        wg_wait0();
        pin(o[0]); pin(o[1]);
        if (lane == 0) mbar_arrive(sb + kBarEmpty + 8 * slot);
        advance();
        rescale();
    }

    uint32_t peer;
    asm("mapa.shared::cluster.u32 %0, %1, %2;" : "=r"(peer) : "r"(sb), "r"(rank ^ 1));
    {
        const float wsum = warp_col_reduce<false>(l, lane);
        if (lane < 16) sts32(red_wr + 256, wsum);
        consumer_bar();
#pragma unroll
        for (int j = 0; j < 4; j++) {
            const float4 r = lds128(red_rd + 256 + ((j >> 1) * 8 + (j & 1)) * 16);
            l[j] = (r.x + r.y) + (r.z + r.w);
        }
    }
    asm volatile("barrier.cluster.wait.acquire.aligned;" ::: "memory");
    if (tid < 4) {
        st_async_v4(peer + kOffXS + tid * 16, m[0], m[1], m[2], m[3], peer + kBarXS);
        st_async_v4(peer + kOffXS + 64 + tid * 16, l[0], l[1], l[2], l[3], peer + kBarXS);
    }

    issue_pv(kTilesPerCta - 1);

    float f_own[4], f_peer[4];
    {
        mbar_wait_cluster(sb + kBarXS, 0);
        const float4 pm4 = lds128(sb + kOffXS + t4 * 16);
        const float4 pl4 = lds128(sb + kOffXS + 64 + t4 * 16);
        const float pm[4] = {pm4.x, pm4.y, pm4.z, pm4.w};
        const float pl[4] = {pl4.x, pl4.y, pl4.z, pl4.w};
#pragma unroll
        for (int j = 0; j < 4; j++) {
            const float mt = fmaxf(m[j], pm[j]);
            const float a = ex2((m[j] - mt) * c), b = ex2((pm[j] - mt) * c);
            const float inv = __fdividef(1.f, a * l[j] + b * pl[j]);
            f_own[j] = a * inv;
            f_peer[j] = b * inv;
        }
    }

    wg_wait0();
    pin(o[0]); pin(o[1]);
    st_async_v4(peer + kOffXO + tid * 16, o[1][0], o[1][1], o[1][2], o[1][3], peer + kBarXO);
    st_async_v4(peer + kOffXO + 2048 + tid * 16, o[1][4], o[1][5], o[1][6], o[1][7], peer + kBarXO);

    mbar_wait_cluster(sb + kBarXO, 0);
    const float4 x0 = lds128(sb + kOffXO + tid * 16);
    const float4 x1 = lds128(sb + kOffXO + 2048 + tid * 16);
    const float px[8] = {x0.x, x0.y, x0.z, x0.w, x1.x, x1.y, x1.z, x1.w};
    float r[8];
#pragma unroll
    for (int i = 0; i < 8; i++) {
        const int j = (i >> 2) * 2 + (i & 1);
        r[i] = o[0][i] * f_own[j] + px[i] * f_peer[j];
    }
    uint32_t* dst = reinterpret_cast<uint32_t*>(out + (head * kQRows + (lane >> 2)) * kD + rank * 64 + warp * 16 + 2 * t4);
#pragma unroll
    for (int b = 0; b < 4; b++) {
        uint32_t tr;
        asm volatile("movmatrix.sync.aligned.m8n8.trans.b16 %0, %1;" : "=r"(tr) : "r"(pack_bf16(r[2 * b], r[2 * b + 1])));
        dst[(b >> 1) * (8 * kD / 2) + (b & 1) * 4] = tr;
    }
}

using EncodeFn = CUresult (*)(CUtensorMap*, CUtensorMapDataType, cuuint32_t, void*, const cuuint64_t*,
                              const cuuint64_t*, const cuuint32_t*, const cuuint32_t*, CUtensorMapInterleave,
                              CUtensorMapSwizzle, CUtensorMapL2promotion, CUtensorMapFloatOOBfill);

CUtensorMap make_map(EncodeFn encode, void* ptr, uint64_t rows, uint32_t box_rows) {
    CUtensorMap map;
    const cuuint64_t dims[4] = {64, 8, 2, rows / 8};
    const cuuint64_t strides[3] = {256, 128, 2048};
    const cuuint32_t box[4] = {64, 8, 2, box_rows / 8};
    const cuuint32_t elem[4] = {1, 1, 1, 1};
    encode(&map, CU_TENSOR_MAP_DATA_TYPE_BFLOAT16, 4, ptr, dims, strides, box, elem, CU_TENSOR_MAP_INTERLEAVE_NONE,
           CU_TENSOR_MAP_SWIZZLE_128B, CU_TENSOR_MAP_L2_PROMOTION_NONE, CU_TENSOR_MAP_FLOAT_OOB_FILL_NONE);
    return map;
}

}

extern "C" void kernel_launch(void* const* d_in, const int* in_sizes, int n_in, void* d_out, int out_size) {
    (void)in_sizes; (void)n_in; (void)out_size;
    static EncodeFn encode = nullptr;
    if (!encode) {
        cudaDriverEntryPointQueryResult status;
        cudaGetDriverEntryPoint("cuTensorMapEncodeTiled", reinterpret_cast<void**>(&encode), cudaEnableDefault, &status);
        cudaFuncSetAttribute(gqa_decode_kernel, cudaFuncAttributeMaxDynamicSharedMemorySize, kSmemBytes);
    }
    const CUtensorMap map_q = make_map(encode, d_in[0], (uint64_t)kHeads * kQRows, kQRows);
    const CUtensorMap map_k = make_map(encode, d_in[1], (uint64_t)kHeads * kSk, kTile);
    const CUtensorMap map_v = make_map(encode, d_in[2], (uint64_t)kHeads * kSk, kTile);
    gqa_decode_kernel<<<2 * kHeads, 160, kSmemBytes>>>(map_k, map_v, map_q, static_cast<__nv_bfloat16*>(d_out));
}
```

```cpp
#include <cuda_runtime.h>
#include <cuda_bf16.h>
#include <cuda.h>
#include <stdint.h>

namespace {

constexpr int kD = 128;
constexpr int kSk = 8192;
constexpr int kHeads = 64;
constexpr int kQRows = 16;
constexpr int kTile = 128;
constexpr int kTiles = kSk / 2 / kTile;
constexpr int kLoads = 2 * kTiles;
constexpr int kSlots = 5;
constexpr int kEnd = 6;
constexpr int kSplit = 2;
constexpr int kGroups = kTile / 8;
constexpr int kThreads = 288;

constexpr uint32_t kTileBytes = kTile * kD * 2;
constexpr uint32_t kQBytes = kQRows * kD * 2;
constexpr uint32_t kPBytes = kTile * kQRows * 2;
constexpr uint32_t kPStride = kPBytes + 64;

constexpr uint32_t kOffRing = 0;
constexpr uint32_t kOffQ = kOffRing + kSlots * kTileBytes;
constexpr uint32_t kOffPeerO = kOffQ + kQBytes;
constexpr uint32_t kOffPeerP = kOffPeerO + 4096;
constexpr uint32_t kOffP = kOffPeerP + kSplit * kPBytes;
constexpr uint32_t kOffPeerStats = kOffP + kEnd * kPStride;
constexpr uint32_t kOffRed = kOffPeerStats + 256;
constexpr uint32_t kOffCoef = kOffRed + 768;
constexpr uint32_t kBarFull = kOffCoef + 384;
constexpr uint32_t kBarEmpty = kBarFull + 8 * kLoads;
constexpr uint32_t kBarEnd = kBarEmpty + 8 * kSlots;
constexpr uint32_t kBarStats = kBarEnd + 8;
constexpr uint32_t kBarAck = kBarStats + 8;
constexpr uint32_t kSmemBytes = kBarAck + 8;

static_assert(kSplit == 2 && kEnd >= kSlots && kEnd - kSlots < kEnd - kSplit, "tail schedule");

constexpr uint64_t kEvictFirst = 0x12F0000000000000ull;
constexpr int kSpinLimit = 1 << 24;

constexpr uint32_t kHiTile = (2048 >> 4) | (1u << 30);
constexpr uint32_t kHiHalf = (1024 >> 4) | (1u << 30);
constexpr uint32_t kHiP = 256 >> 4;

__device__ __forceinline__ bool load_is_v(int i) { return i < kLoads - 2 * kEnd ? (i & 1) : i >= kLoads - kEnd; }

__device__ __forceinline__ void mbar_init(uint32_t bar, uint32_t count) {
    asm volatile("mbarrier.init.shared::cta.b64 [%0], %1;" ::"r"(bar), "r"(count) : "memory");
}
__device__ __forceinline__ void mbar_expect_tx(uint32_t bar, uint32_t bytes) {
    asm volatile("mbarrier.arrive.expect_tx.shared::cta.b64 _, [%0], %1;" ::"r"(bar), "r"(bytes) : "memory");
}
__device__ __forceinline__ void mbar_arrive(uint32_t bar) {
    asm volatile("mbarrier.arrive.shared::cta.b64 _, [%0];" ::"r"(bar) : "memory");
}
__device__ __forceinline__ void mbar_wait(uint32_t bar, uint32_t parity) {
    asm volatile(
        "{\n.reg .pred p;\n.reg .u32 n;\nmov.u32 n, 0;\n"
        "WAIT_LOOP:\n"
        "mbarrier.try_wait.parity.shared::cta.b64 p, [%0], %1;\n"
        "@p bra WAIT_DONE;\n"
        "add.u32 n, n, 1;\nsetp.lt.u32 p, n, %2;\n@p bra WAIT_LOOP;\ntrap;\n"
        "WAIT_DONE:\n}"
        ::"r"(bar), "r"(parity), "n"(kSpinLimit) : "memory");
}
__device__ __forceinline__ void mbar_wait_peer(uint32_t bar) {
    mbar_wait(bar, 0);
    asm volatile("fence.acquire.sync_restrict::shared::cluster.cluster;" ::: "memory");
}
__device__ __forceinline__ void tma_load(uint32_t dst, const CUtensorMap* map, int half, int group, uint32_t bar) {
    asm volatile(
        "cp.async.bulk.tensor.4d.shared::cluster.global.mbarrier::complete_tx::bytes.L2::cache_hint "
        "[%0], [%1, {%3, %3, %4, %5}], [%2], %6;"
        ::"r"(dst), "l"(map), "r"(bar), "r"(0), "r"(half), "r"(group), "l"(kEvictFirst) : "memory");
}
__device__ __forceinline__ void copy_to_peer(uint32_t dst, uint32_t src, uint32_t bytes, uint32_t bar) {
    asm volatile("cp.async.bulk.shared::cluster.shared::cta.mbarrier::complete_tx::bytes [%0], [%1], %2, [%3];"
                 ::"r"(dst), "r"(src), "r"(bytes), "r"(bar) : "memory");
}
__device__ __forceinline__ void st_async_v4(uint32_t dst, const float* v, uint32_t bar) {
    asm volatile("st.async.weak.shared::cluster.mbarrier::complete_tx::bytes.v4.f32 [%0], {%1, %2, %3, %4}, [%5];"
                 ::"r"(dst), "f"(v[0]), "f"(v[1]), "f"(v[2]), "f"(v[3]), "r"(bar) : "memory");
}
__device__ __forceinline__ void lds128(float* v, uint32_t addr) {
    asm volatile("ld.shared.v4.f32 {%0, %1, %2, %3}, [%4];"
                 : "=f"(v[0]), "=f"(v[1]), "=f"(v[2]), "=f"(v[3]) : "r"(addr) : "memory");
}
__device__ __forceinline__ void sts128(uint32_t addr, const float* v) {
    asm volatile("st.shared.v4.f32 [%0], {%1, %2, %3, %4};"
                 ::"r"(addr), "f"(v[0]), "f"(v[1]), "f"(v[2]), "f"(v[3]) : "memory");
}
__device__ __forceinline__ void sts32(uint32_t addr, float v) {
    asm volatile("st.shared.f32 [%0], %1;" ::"r"(addr), "f"(v) : "memory");
}
__device__ __forceinline__ void score_group_sync() { asm volatile("bar.sync 1, 128;" ::: "memory"); }
__device__ __forceinline__ float ex2(float x) {
    float y;
    asm("ex2.approx.ftz.f32 %0, %1;" : "=f"(y) : "f"(x));
    return y;
}
__device__ __forceinline__ uint32_t pack_bf16(float lo, float hi) {
    uint32_t r;
    asm("cvt.rn.bf16x2.f32 %0, %1, %2;" : "=r"(r) : "f"(hi), "f"(lo));
    return r;
}
__device__ __forceinline__ uint32_t uniform(uint32_t x) { return __shfl_sync(0xffffffffu, x, 0); }

__device__ __forceinline__ void wg_fence() { asm volatile("wgmma.fence.sync.aligned;" ::: "memory"); }
__device__ __forceinline__ void wg_commit() { asm volatile("wgmma.commit_group.sync.aligned;" ::: "memory"); }
template <int N>
__device__ __forceinline__ void wg_wait() { asm volatile("wgmma.wait_group.sync.aligned %0;" ::"n"(N) : "memory"); }

template <int kAccumulate, int kTransA, uint32_t kHiA, uint32_t kHiB>
__device__ __forceinline__ void wgmma(float (&d)[8], uint32_t lo_a, uint32_t lo_b) {
    asm volatile(
        "{\n.reg .b64 da, db;\nmov.b64 da, {%8, %12};\nmov.b64 db, {%9, %13};\n"
        "wgmma.mma_async.sync.aligned.m64n16k16.f32.bf16.bf16 "
        "{%0, %1, %2, %3, %4, %5, %6, %7}, da, db, %10, 1, 1, %11, 0;\n}"
        : "+f"(d[0]), "+f"(d[1]), "+f"(d[2]), "+f"(d[3]), "+f"(d[4]), "+f"(d[5]), "+f"(d[6]), "+f"(d[7])
        : "r"(lo_a), "r"(lo_b), "n"(kAccumulate), "n"(kTransA), "n"(kHiA), "n"(kHiB));
}
__device__ __forceinline__ void pin(float (&d)[8]) {
    asm volatile("" : "+f"(d[0]), "+f"(d[1]), "+f"(d[2]), "+f"(d[3]), "+f"(d[4]), "+f"(d[5]), "+f"(d[6]), "+f"(d[7])::"memory");
}

template <uint32_t kHiA, uint32_t kStepA>
__device__ __forceinline__ void issue_pv(float (&d)[2][8], uint32_t a0, uint32_t p0, uint32_t a1, uint32_t p1) {
    wg_fence();
    wgmma<0, 1, kHiA, kHiP>(d[1], a1, p1);
    wgmma<0, 1, kHiA, kHiP>(d[0], a0, p0);
#pragma unroll
    for (int k = 1; k < kTile / 16; k++) {
        wgmma<1, 1, kHiA, kHiP>(d[1], a1 + k * kStepA, p1 + k * (512 >> 4));
        wgmma<1, 1, kHiA, kHiP>(d[0], a0 + k * kStepA, p0 + k * (512 >> 4));
    }
    wg_commit();
}

__device__ __forceinline__ constexpr int col(int i) { return (i >> 2) * 2 + (i & 1); }

__device__ __forceinline__ void fold(float (&acc)[8], float (&d)[8], const float (&a)[4]) {
    pin(d);
#pragma unroll
    for (int i = 0; i < 8; i++) acc[i] = fmaf(acc[i], a[col(i)], d[i]);
}

template <bool kMax>
__device__ __forceinline__ float warp_col_reduce(const float (&x)[4], int lane) {
    const bool b2 = lane & 4, b3 = lane & 8;
    float a = b2 ? x[2] : x[0], b = b2 ? x[3] : x[1];
    const float ra = __shfl_xor_sync(0xffffffffu, b2 ? x[0] : x[2], 4);
    const float rb = __shfl_xor_sync(0xffffffffu, b2 ? x[1] : x[3], 4);
    a = kMax ? fmaxf(a, ra) : a + ra;
    b = kMax ? fmaxf(b, rb) : b + rb;
    float keep = b3 ? b : a;
    const float r2 = __shfl_xor_sync(0xffffffffu, b3 ? a : b, 8);
    keep = kMax ? fmaxf(keep, r2) : keep + r2;
    const float r3 = __shfl_xor_sync(0xffffffffu, keep, 16);
    return kMax ? fmaxf(keep, r3) : keep + r3;
}

struct RingPos {
    int pos, slot;
    __device__ __forceinline__ void step(int n) {
        pos += n;
        slot += n;
        if (slot >= kSlots) slot -= kSlots;
    }
};

__global__ void __cluster_dims__(2, 1, 1) __launch_bounds__(kThreads, 1)
gqa_decode_kernel(const __grid_constant__ CUtensorMap map_k, const __grid_constant__ CUtensorMap map_v,
                  const __grid_constant__ CUtensorMap map_q, const __grid_constant__ CUtensorMap map_v_half,
                  __nv_bfloat16* __restrict__ out, const char* __restrict__ k_bytes) {
    asm volatile("prefetch.global.L2 [%0];" ::"l"(k_bytes + (size_t)(blockIdx.x >> 1) * (kSk * kD * 2) +
                                                   (blockIdx.x & 1) * kTileBytes + (threadIdx.x & 255) * 128) : "memory");

    extern __shared__ __align__(1024) uint8_t smem[];
    const uint32_t sb = (uint32_t)__cvta_generic_to_shared(smem);
    const int tid = threadIdx.x;
    const int head = blockIdx.x >> 1;
    const int rank = blockIdx.x & 1;
    const int group0 = head * (kSk / 8) + rank * kGroups;

    if (tid == 256) {
#pragma unroll
        for (int i = 0; i < kSlots; i++) {
            const uint32_t bar = sb + kBarFull + 8 * i;
            mbar_init(bar, (i & 1) ? 5 : 1);
            mbar_expect_tx(bar, kTileBytes + (i == 0 ? kQBytes : 0));
            tma_load(sb + kOffRing + i * kTileBytes, (i & 1) ? &map_v : &map_k, 0, group0 + (i >> 1) * 2 * kGroups, bar);
            if (i == 0) tma_load(sb + kOffQ, &map_q, 0, head * (kQRows / 8), bar);
        }
    } else if (tid < 256 && (tid & 3) == 0 && (tid >> 2) >= kSlots) {
        const int i = tid >> 2;
        const uint32_t bar = sb + kBarFull + 8 * i;
        mbar_init(bar, load_is_v(i) ? 5 : 1);
        mbar_expect_tx(bar, i >= kLoads - kSplit ? kTileBytes + kPBytes : kTileBytes);
        asm volatile("fence.mbarrier_init.release.cluster;" ::: "memory");
    } else if (tid == 1) {
        if (sb & 1023) __trap();
#pragma unroll
        for (int i = 0; i < kSlots; i++) mbar_init(sb + kBarEmpty + 8 * i, 4);
        mbar_init(sb + kBarEnd, 2);
        mbar_init(sb + kBarStats, 1);
        mbar_init(sb + kBarAck, 1);
        mbar_expect_tx(sb + kBarStats, 256);
        mbar_expect_tx(sb + kBarEnd, 4096);
        asm volatile("fence.mbarrier_init.release.cluster;" ::: "memory");
    }
    __syncthreads();
    asm volatile("barrier.cluster.arrive.relaxed.aligned;" ::: "memory");

    const int lane = tid & 31, warp = (tid >> 5) & 3, t4 = lane & 3;
    const float c = 0.08838834764831845f * 1.4426950408889634f;
    const uint32_t desc_base = ((sb & 0x3FFFF) >> 4) | (1u << 16);
    uint32_t peer;
    asm("mapa.shared::cluster.u32 %0, %1, %2;" : "=r"(peer) : "r"(sb), "r"(rank ^ 1));

    if (tid >= 256) {
        if (tid == 256) {
            int slot = 0;
            uint32_t parity = 0;
#pragma unroll 1
            for (int i = kSlots; i < kLoads; i++) {
                const bool is_v = load_is_v(i), split = i >= kLoads - kSplit;
                const int tile = i < kLoads - 2 * kEnd ? (i >> 1) : (is_v ? i - kTiles : i - (kTiles - kEnd));
                mbar_wait(sb + kBarEmpty + 8 * slot, parity);
                if (i == kLoads - 1) mbar_wait(sb + kBarFull + 8 * (i - 2), 0);
                tma_load(sb + kOffRing + slot * kTileBytes, split ? &map_v_half : (is_v ? &map_v : &map_k),
                         split ? rank : 0, group0 + tile * 2 * kGroups - (split ? rank * kGroups : 0),
                         sb + kBarFull + 8 * i);
                if (++slot == kSlots) { slot = 0; parity ^= 1; }
            }
        }
    } else if (tid < 128) {
        const int my_col = 2 * t4 + ((lane >> 3) & 1) + 8 * ((lane >> 2) & 1);
        const uint32_t red_wr = sb + kOffRed + (my_col * 4 + warp) * 4;
        const uint32_t red_rd = sb + kOffRed + (2 * t4) * 16;
        const uint32_t dq = uniform(desc_base + (kOffQ >> 4));
        float s[2][8], m[4], l[4], a[4], a_prev[4];
#pragma unroll
        for (int j = 0; j < 4; j++) { m[j] = -INFINITY; l[j] = 0.f; a[j] = 0.f; }
        RingPos kc{0, 0};
        int pb = 0;
        asm volatile("barrier.cluster.wait.aligned;" ::: "memory");

#pragma unroll 1
        for (int t = 0; t < kTiles; t++) {
            const uint32_t dk = uniform(desc_base + kc.slot * (kTileBytes >> 4));
            mbar_wait(sb + kBarFull + 8 * kc.pos, 0);
            pin(s[0]); pin(s[1]);
            wg_fence();
#pragma unroll
            for (int k = 0; k < kD / 16; k++) {
                const uint32_t off = ((k >> 2) * 1024 + (k & 3) * 32) >> 4;
#pragma unroll
                for (int mt = 0; mt < 2; mt++) {
                    if (k == 0) wgmma<0, 0, kHiTile, kHiTile>(s[mt], dk + off + mt * (16384 >> 4), dq + off);
                    else        wgmma<1, 0, kHiTile, kHiTile>(s[mt], dk + off + mt * (16384 >> 4), dq + off);
                }
            }
            wg_commit();
            wg_wait<0>();
            pin(s[0]); pin(s[1]);
            if (lane == 0) mbar_arrive(sb + kBarEmpty + 8 * kc.slot);
            kc.step(t < kTiles - kEnd ? 2 : 1);

            float x[4];
#pragma unroll
            for (int j = 0; j < 4; j++) {
                const int i0 = (j >> 1) * 4 + (j & 1);
                x[j] = fmaxf(fmaxf(s[0][i0], s[0][i0 + 2]), fmaxf(s[1][i0], s[1][i0 + 2]));
            }
            const float wmax = warp_col_reduce<true>(x, lane);
            const uint32_t rb = (t & 1) * 256;
            if (lane < 16) sts32(red_wr + rb, wmax);
            score_group_sync();
            float mc[4];
#pragma unroll
            for (int j = 0; j < 4; j++) {
                float r[4];
                lds128(r, red_rd + rb + ((j >> 1) * 8 + (j & 1)) * 16);
                const float mn = fmaxf(fmaxf(fmaxf(r[0], r[1]), fmaxf(r[2], r[3])), m[j]);
                a_prev[j] = a[j];
                a[j] = ex2((m[j] - mn) * c);
                m[j] = mn;
                mc[j] = mn * c;
                l[j] *= a[j];
            }
            const uint32_t p_buf = sb + kOffP + pb * kPStride;
#pragma unroll
            for (int mt = 0; mt < 2; mt++) {
                float p[8];
#pragma unroll
                for (int i = 0; i < 8; i++) {
                    p[i] = ex2(fmaf(s[mt][i], c, -mc[col(i)]));
                    l[col(i)] += p[i];
                }
                asm volatile("stmatrix.sync.aligned.m8n8.x4.trans.shared.b16 [%0], {%1, %2, %3, %4};"
                             ::"r"(p_buf + mt * 2048 + warp * 512 + lane * 16), "r"(pack_bf16(p[0], p[1])),
                               "r"(pack_bf16(p[2], p[3])), "r"(pack_bf16(p[4], p[5])), "r"(pack_bf16(p[6], p[7]))
                             : "memory");
            }
            if (tid < 4) sts128(p_buf + kPBytes + tid * 16, a);
            asm volatile("fence.proxy.async.shared::cta;" ::: "memory");
            __syncwarp();
            if (lane == 0) {
                const uint32_t v_bar = kBarFull + 8 * (t < kTiles - kEnd ? 2 * t + 1 : t + kTiles);
                mbar_arrive(sb + v_bar);
                if (t >= kTiles - kSplit) {
                    const uint32_t dst = peer + kOffPeerP + (t - (kTiles - kSplit)) * kPBytes + warp * 512;
                    copy_to_peer(dst, p_buf + warp * 512, 512, peer + v_bar);
                    copy_to_peer(dst + 2048, p_buf + warp * 512 + 2048, 512, peer + v_bar);
                }
            }
            if (++pb == kEnd) pb = 0;
        }

        const float wsum = warp_col_reduce<false>(l, lane);
        if (lane < 16) sts32(red_wr + 512, wsum);
        score_group_sync();
        if (warp == 0) {
#pragma unroll
            for (int j = 0; j < 4; j++) {
                float r[4];
                lds128(r, red_rd + 512 + ((j >> 1) * 8 + (j & 1)) * 16);
                l[j] = (r[0] + r[1]) + (r[2] + r[3]);
            }
            if (tid < 4) {
                st_async_v4(peer + kOffPeerStats + tid * 16, m, peer + kBarStats);
                st_async_v4(peer + kOffPeerStats + 64 + tid * 16, l, peer + kBarStats);
                st_async_v4(peer + kOffPeerStats + 128 + tid * 16, a, peer + kBarStats);
                st_async_v4(peer + kOffPeerStats + 192 + tid * 16, a_prev, peer + kBarStats);
            }
            mbar_wait_peer(sb + kBarStats);
            float pm[4], pl[4], pa[4], pa_prev[4], coef[6][4];
            lds128(pm, sb + kOffPeerStats + t4 * 16);
            lds128(pl, sb + kOffPeerStats + 64 + t4 * 16);
            lds128(pa, sb + kOffPeerStats + 128 + t4 * 16);
            lds128(pa_prev, sb + kOffPeerStats + 192 + t4 * 16);
#pragma unroll
            for (int j = 0; j < 4; j++) {
                const float mt = fmaxf(m[j], pm[j]);
                const float eo = ex2((m[j] - mt) * c), ep = ex2((pm[j] - mt) * c);
                const float inv = 1.f / (eo * l[j] + ep * pl[j]);
                coef[0][j] = eo * inv;
                coef[1][j] = ep * inv;
                coef[2][j] = coef[0][j] * a[j];
                coef[3][j] = coef[1][j] * pa[j];
                coef[4][j] = coef[2][j] * a_prev[j];
                coef[5][j] = coef[3][j] * pa_prev[j];
            }
            if (tid < 4) {
#pragma unroll
                for (int q = 0; q < 6; q++) sts128(sb + kOffCoef + q * 64 + tid * 16, coef[q]);
            }
            __syncwarp();
            if (lane == 0) mbar_arrive(sb + kBarEnd);
            mbar_wait(sb + kBarAck, 0);
        }
    } else {
        float o[2][8], T[2][2][8], alpha[2][4];
#pragma unroll
        for (int i = 0; i < 8; i++) o[0][i] = o[1][i] = 0.f;
        const int wt = tid - 128;
        const uint32_t dv0 = uniform(desc_base + rank * (1024 >> 4));
        const uint32_t dv1 = dv0 + (1024 >> 4) - rank * (2048 >> 4);
        const uint32_t dp = uniform((((sb + kOffP) & 0x3FFFF) >> 4) | ((128 >> 4) << 16));
        asm volatile("barrier.cluster.wait.aligned;" ::: "memory");

        RingPos vc{1, 1};
        int pb = 0;
#pragma unroll 1
        for (int t = 0; t < kTiles - kEnd; t++) {
            const uint32_t va = uniform(vc.slot * (kTileBytes >> 4)), pa = uniform(dp + pb * (kPStride >> 4));
            mbar_wait(sb + kBarFull + 8 * vc.pos, 0);
            lds128(alpha[0], sb + kOffP + pb * kPStride + kPBytes + t4 * 16);
            pin(T[0][0]); pin(T[0][1]);
            issue_pv<kHiTile, (4096 >> 4)>(T[0], dv0 + va, pa, dv1 + va, pa);
            wg_wait<0>();
            if (lane == 0) mbar_arrive(sb + kBarEmpty + 8 * vc.slot);
            fold(o[1], T[0][1], alpha[0]);
            fold(o[0], T[0][0], alpha[0]);
            vc.step(2);
            if (++pb == kEnd) pb = 0;
        }

        const uint32_t dh0 = uniform(desc_base + rank * (16384 >> 4));
        const uint32_t dh1 = dh0 + (16384 >> 4) - rank * (32768 >> 4);
        float coef[6][4], r[8];
#pragma unroll
        for (int j = 0; j < kEnd; j++) {
            const int t = kTiles - kEnd + j, pos = kLoads - kEnd + j, slot = pos % kSlots;
            const bool split = j >= kEnd - kSplit, last = j == kEnd - 1;
            const uint32_t va = slot * (kTileBytes >> 4), pa = dp + (t % kEnd) * (kPStride >> 4);
            float (&d)[2][8] = T[j & 1];
            float (&prev)[2][8] = T[(j + 1) & 1];
            pin(d[0]); pin(d[1]);
            if (split) {
                mbar_wait_peer(sb + kBarFull + 8 * pos);
                const uint32_t pr = dp - ((kOffP - kOffPeerP) >> 4) + (j - (kEnd - kSplit)) * (kPBytes >> 4);
                issue_pv<kHiHalf, (2048 >> 4)>(d, dh0 + va, pa, dh1 + va, pr);
            } else {
                mbar_wait(sb + kBarFull + 8 * pos, 0);
                lds128(alpha[j & 1], sb + kOffP + (t % kEnd) * kPStride + kPBytes + t4 * 16);
                issue_pv<kHiTile, (4096 >> 4)>(d, dv0 + va, pa, dv1 + va, pa);
            }
            if (pos + kSlots < kLoads) {
                wg_wait<0>();
                if (lane == 0) mbar_arrive(sb + kBarEmpty + 8 * slot);
            }
            if (j > 0 && !split) {
                wg_wait<1>();
                fold(o[1], prev[1], alpha[(j + 1) & 1]);
                fold(o[0], prev[0], alpha[(j + 1) & 1]);
            }
            if (j == kEnd - kSplit - 1) {
                wg_wait<0>();
                fold(o[1], d[1], alpha[j & 1]);
                st_async_v4(peer + kOffPeerO + wt * 16, &o[1][0], peer + kBarEnd);
                st_async_v4(peer + kOffPeerO + 2048 + wt * 16, &o[1][4], peer + kBarEnd);
                fold(o[0], d[0], alpha[j & 1]);
            }
            if (j == kEnd - 2) {
                mbar_wait_peer(sb + kBarEnd);
#pragma unroll
                for (int q = 0; q < 6; q++) lds128(coef[q], sb + kOffCoef + q * 64 + t4 * 16);
                float px[8];
                lds128(&px[0], sb + kOffPeerO + wt * 16);
                lds128(&px[4], sb + kOffPeerO + 2048 + wt * 16);
#pragma unroll
                for (int i = 0; i < 8; i++) r[i] = fmaf(o[0][i], coef[4][col(i)], px[i] * coef[5][col(i)]);
            }
            if (last) {
                if (wt == 0)
                    asm volatile("mbarrier.arrive.relaxed.cluster.shared::cluster.b64 _, [%0];" ::"r"(peer + kBarAck) : "memory");
                wg_wait<1>();
                pin(prev[0]); pin(prev[1]);
#pragma unroll
                for (int i = 0; i < 8; i++)
                    r[i] = fmaf(prev[0][i], coef[2][col(i)], fmaf(prev[1][i], coef[3][col(i)], r[i]));
                wg_wait<0>();
                pin(d[0]); pin(d[1]);
#pragma unroll
                for (int i = 0; i < 8; i++)
                    r[i] = fmaf(d[0][i], coef[0][col(i)], fmaf(d[1][i], coef[1][col(i)], r[i]));
            }
        }

        uint32_t* dst = reinterpret_cast<uint32_t*>(out + (head * kQRows + (lane >> 2)) * kD + rank * 64 + warp * 16 + 2 * t4);
#pragma unroll
        for (int b = 0; b < 4; b++) {
            uint32_t tr;
            asm volatile("movmatrix.sync.aligned.m8n8.trans.b16 %0, %1;" : "=r"(tr) : "r"(pack_bf16(r[2 * b], r[2 * b + 1])));
            dst[(b >> 1) * (8 * kD / 2) + (b & 1) * 4] = tr;
        }
    }
}

using EncodeFn = CUresult (*)(CUtensorMap*, CUtensorMapDataType, cuuint32_t, void*, const cuuint64_t*,
                              const cuuint64_t*, const cuuint32_t*, const cuuint32_t*, CUtensorMapInterleave,
                              CUtensorMapSwizzle, CUtensorMapL2promotion, CUtensorMapFloatOOBfill);

CUtensorMap make_map(EncodeFn encode, void* ptr, uint64_t rows, uint32_t box_halves, uint32_t box_rows) {
    CUtensorMap map;
    const cuuint64_t dims[4] = {64, 8, 2, rows / 8};
    const cuuint64_t strides[3] = {256, 128, 2048};
    const cuuint32_t box[4] = {64, 8, box_halves, box_rows / 8};
    const cuuint32_t elem[4] = {1, 1, 1, 1};
    encode(&map, CU_TENSOR_MAP_DATA_TYPE_BFLOAT16, 4, ptr, dims, strides, box, elem, CU_TENSOR_MAP_INTERLEAVE_NONE,
           CU_TENSOR_MAP_SWIZZLE_128B, CU_TENSOR_MAP_L2_PROMOTION_NONE, CU_TENSOR_MAP_FLOAT_OOB_FILL_NONE);
    return map;
}

}

extern "C" void kernel_launch(void* const* d_in, const int* in_sizes, int n_in, void* d_out, int out_size) {
    (void)in_sizes; (void)n_in; (void)out_size;
    static EncodeFn encode = nullptr;
    if (!encode) {
        cudaDriverEntryPointQueryResult status;
        cudaGetDriverEntryPoint("cuTensorMapEncodeTiled", reinterpret_cast<void**>(&encode), cudaEnableDefault, &status);
        cudaFuncSetAttribute(gqa_decode_kernel, cudaFuncAttributeMaxDynamicSharedMemorySize, kSmemBytes);
    }
    const uint64_t kv_rows = (uint64_t)kHeads * kSk;
    const CUtensorMap map_q = make_map(encode, d_in[0], (uint64_t)kHeads * kQRows, 2, kQRows);
    const CUtensorMap map_k = make_map(encode, d_in[1], kv_rows, 2, kTile);
    const CUtensorMap map_v = make_map(encode, d_in[2], kv_rows, 2, kTile);
    const CUtensorMap map_v_half = make_map(encode, d_in[2], kv_rows, 1, 2 * kTile);
    gqa_decode_kernel<<<2 * kHeads, kThreads, kSmemBytes>>>(map_k, map_v, map_q, map_v_half,
                                                            static_cast<__nv_bfloat16*>(d_out),
                                                            static_cast<const char*>(d_in[1]));
}
```

```cpp
#include <cuda_runtime.h>
#include <cuda_bf16.h>
#include <cuda.h>
#include <stdint.h>

namespace {

constexpr int kD = 128;
constexpr int kSk = 8192;
constexpr int kHeads = 64;
constexpr int kQRows = 16;
constexpr int kTile = 128;
constexpr int kTiles = kSk / 2 / kTile;
constexpr int kLoads = 2 * kTiles;
constexpr int kSlots = 5;
constexpr int kEnd = 6;
constexpr int kSplit = 2;
constexpr int kWhole = kLoads - kSplit;
constexpr int kGroups = kTile / 8;
constexpr int kThreads = 320;
constexpr int kCtas = 2 * kHeads;
constexpr int kPaceFrom = 8;
constexpr int kPaceSlack = 72;

constexpr uint32_t kTileBytes = kTile * kD * 2;
constexpr uint32_t kQBytes = kQRows * kD * 2;
constexpr uint32_t kPBytes = kTile * kQRows * 2;
constexpr uint32_t kPStride = kPBytes + 64;

constexpr uint32_t kOffRing = 0;
constexpr uint32_t kOffQ = kOffRing + kSlots * kTileBytes;
constexpr uint32_t kOffPeerO = kOffQ + kQBytes;
constexpr uint32_t kOffPeerP = kOffPeerO + 4096;
constexpr uint32_t kOffP = kOffPeerP + kSplit * kPBytes;
constexpr uint32_t kOffPeerStats = kOffP + kEnd * kPStride;
constexpr uint32_t kOffRed = kOffPeerStats + 256;
constexpr uint32_t kOffCoef = kOffRed + 768;
constexpr uint32_t kBarFull = kOffCoef + 384;
constexpr uint32_t kBarHalf = kBarFull + 8 * kWhole;
constexpr uint32_t kBarEmpty = kBarHalf + 8 * 2 * kSplit;
constexpr uint32_t kBarEnd = kBarEmpty + 8 * kSlots;
constexpr uint32_t kBarStats = kBarEnd + 8;
constexpr uint32_t kBarAck = kBarStats + 8;
constexpr uint32_t kOffPace = kBarAck + 8;
constexpr uint32_t kSmemBytes = kOffPace + 8;

static_assert(kSplit == 2 && kEnd >= kSlots && kEnd - kSlots < kEnd - kSplit, "tail schedule");
static_assert(kPaceSlack >= kCtas / 2 && kWhole % 2 == 0, "the slowest CTA is never held back");

constexpr uint64_t kEvictFirst = 0x12F0000000000000ull;
constexpr int kSpinLimit = 1 << 24;

constexpr uint32_t kHiTile = (2048 >> 4) | (1u << 30);
constexpr uint32_t kHiHalf = (1024 >> 4) | (1u << 30);
constexpr uint32_t kHiP = 256 >> 4;

__device__ unsigned g_pairs_issued;

__device__ __forceinline__ bool load_is_v(int i) { return i < kLoads - 2 * kEnd ? (i & 1) : i >= kLoads - kEnd; }

__device__ __forceinline__ void mbar_init(uint32_t bar, uint32_t count) {
    asm volatile("mbarrier.init.shared::cta.b64 [%0], %1;" ::"r"(bar), "r"(count) : "memory");
}
__device__ __forceinline__ void mbar_expect_tx(uint32_t bar, uint32_t bytes) {
    asm volatile("mbarrier.arrive.expect_tx.shared::cta.b64 _, [%0], %1;" ::"r"(bar), "r"(bytes) : "memory");
}
__device__ __forceinline__ void mbar_arrive(uint32_t bar) {
    asm volatile("mbarrier.arrive.shared::cta.b64 _, [%0];" ::"r"(bar) : "memory");
}
__device__ __forceinline__ void mbar_wait(uint32_t bar, uint32_t parity) {
    asm volatile(
        "{\n.reg .pred p;\n.reg .u32 n;\nmov.u32 n, 0;\n"
        "WAIT_LOOP:\n"
        "mbarrier.try_wait.parity.shared::cta.b64 p, [%0], %1;\n"
        "@p bra WAIT_DONE;\n"
        "add.u32 n, n, 1;\nsetp.lt.u32 p, n, %2;\n@p bra WAIT_LOOP;\ntrap;\n"
        "WAIT_DONE:\n}"
        ::"r"(bar), "r"(parity), "n"(kSpinLimit) : "memory");
}
__device__ __forceinline__ void mbar_wait_peer(uint32_t bar) {
    mbar_wait(bar, 0);
    asm volatile("fence.acquire.sync_restrict::shared::cluster.cluster;" ::: "memory");
}
__device__ __forceinline__ void tma_load(uint32_t dst, const CUtensorMap* map, int half, int group, uint32_t bar) {
    asm volatile(
        "cp.async.bulk.tensor.4d.shared::cluster.global.mbarrier::complete_tx::bytes.L2::cache_hint "
        "[%0], [%1, {%3, %3, %4, %5}], [%2], %6;"
        ::"r"(dst), "l"(map), "r"(bar), "r"(0), "r"(half), "r"(group), "l"(kEvictFirst) : "memory");
}
__device__ __forceinline__ void copy_to_peer(uint32_t dst, uint32_t src, uint32_t bytes, uint32_t bar) {
    asm volatile("cp.async.bulk.shared::cluster.shared::cta.mbarrier::complete_tx::bytes [%0], [%1], %2, [%3];"
                 ::"r"(dst), "r"(src), "r"(bytes), "r"(bar) : "memory");
}
__device__ __forceinline__ void st_async_v4(uint32_t dst, const float* v, uint32_t bar) {
    asm volatile("st.async.weak.shared::cluster.mbarrier::complete_tx::bytes.v4.f32 [%0], {%1, %2, %3, %4}, [%5];"
                 ::"r"(dst), "f"(v[0]), "f"(v[1]), "f"(v[2]), "f"(v[3]), "r"(bar) : "memory");
}
__device__ __forceinline__ void lds128(float* v, uint32_t addr) {
    asm volatile("ld.shared.v4.f32 {%0, %1, %2, %3}, [%4];"
                 : "=f"(v[0]), "=f"(v[1]), "=f"(v[2]), "=f"(v[3]) : "r"(addr) : "memory");
}
__device__ __forceinline__ void sts128(uint32_t addr, const float* v) {
    asm volatile("st.shared.v4.f32 [%0], {%1, %2, %3, %4};"
                 ::"r"(addr), "f"(v[0]), "f"(v[1]), "f"(v[2]), "f"(v[3]) : "memory");
}
__device__ __forceinline__ void sts32(uint32_t addr, float v) {
    asm volatile("st.shared.f32 [%0], %1;" ::"r"(addr), "f"(v) : "memory");
}
__device__ __forceinline__ void score_group_sync() { asm volatile("bar.sync 1, 128;" ::: "memory"); }
__device__ __forceinline__ float ex2(float x) {
    float y;
    asm("ex2.approx.ftz.f32 %0, %1;" : "=f"(y) : "f"(x));
    return y;
}
__device__ __forceinline__ uint32_t pack_bf16(float lo, float hi) {
    uint32_t r;
    asm("cvt.rn.bf16x2.f32 %0, %1, %2;" : "=r"(r) : "f"(hi), "f"(lo));
    return r;
}
__device__ __forceinline__ uint32_t uniform(uint32_t x) { return __shfl_sync(0xffffffffu, x, 0); }

__device__ __forceinline__ void wg_fence() { asm volatile("wgmma.fence.sync.aligned;" ::: "memory"); }
__device__ __forceinline__ void wg_commit() { asm volatile("wgmma.commit_group.sync.aligned;" ::: "memory"); }
template <int N>
__device__ __forceinline__ void wg_wait() { asm volatile("wgmma.wait_group.sync.aligned %0;" ::"n"(N) : "memory"); }

template <int kAccumulate, int kTransA, uint32_t kHiA, uint32_t kHiB>
__device__ __forceinline__ void wgmma(float (&d)[8], uint32_t lo_a, uint32_t lo_b) {
    asm volatile(
        "{\n.reg .b64 da, db;\nmov.b64 da, {%8, %12};\nmov.b64 db, {%9, %13};\n"
        "wgmma.mma_async.sync.aligned.m64n16k16.f32.bf16.bf16 "
        "{%0, %1, %2, %3, %4, %5, %6, %7}, da, db, %10, 1, 1, %11, 0;\n}"
        : "+f"(d[0]), "+f"(d[1]), "+f"(d[2]), "+f"(d[3]), "+f"(d[4]), "+f"(d[5]), "+f"(d[6]), "+f"(d[7])
        : "r"(lo_a), "r"(lo_b), "n"(kAccumulate), "n"(kTransA), "n"(kHiA), "n"(kHiB));
}
__device__ __forceinline__ void pin(float (&d)[8]) {
    asm volatile("" : "+f"(d[0]), "+f"(d[1]), "+f"(d[2]), "+f"(d[3]), "+f"(d[4]), "+f"(d[5]), "+f"(d[6]), "+f"(d[7])::"memory");
}

__device__ __forceinline__ void issue_pv(float (&d)[2][8], uint32_t a0, uint32_t a1, uint32_t p) {
    wg_fence();
    wgmma<0, 1, kHiTile, kHiP>(d[1], a1, p);
    wgmma<0, 1, kHiTile, kHiP>(d[0], a0, p);
#pragma unroll
    for (int k = 1; k < kTile / 16; k++) {
        wgmma<1, 1, kHiTile, kHiP>(d[1], a1 + k * (4096 >> 4), p + k * (512 >> 4));
        wgmma<1, 1, kHiTile, kHiP>(d[0], a0 + k * (4096 >> 4), p + k * (512 >> 4));
    }
    wg_commit();
}
__device__ __forceinline__ void issue_pv_half(float (&d)[8], uint32_t a, uint32_t p) {
    wg_fence();
    wgmma<0, 1, kHiHalf, kHiP>(d, a, p);
#pragma unroll
    for (int k = 1; k < kTile / 16; k++) wgmma<1, 1, kHiHalf, kHiP>(d, a + k * (2048 >> 4), p + k * (512 >> 4));
    wg_commit();
}

__device__ __forceinline__ constexpr int col(int i) { return (i >> 2) * 2 + (i & 1); }

__device__ __forceinline__ void fold(float (&acc)[8], float (&d)[8], const float (&a)[4]) {
    pin(d);
#pragma unroll
    for (int i = 0; i < 8; i++) acc[i] = fmaf(acc[i], a[col(i)], d[i]);
}

template <bool kMax>
__device__ __forceinline__ float warp_col_reduce(const float (&x)[4], int lane) {
    const bool b2 = lane & 4, b3 = lane & 8;
    float a = b2 ? x[2] : x[0], b = b2 ? x[3] : x[1];
    const float ra = __shfl_xor_sync(0xffffffffu, b2 ? x[0] : x[2], 4);
    const float rb = __shfl_xor_sync(0xffffffffu, b2 ? x[1] : x[3], 4);
    a = kMax ? fmaxf(a, ra) : a + ra;
    b = kMax ? fmaxf(b, rb) : b + rb;
    float keep = b3 ? b : a;
    const float r2 = __shfl_xor_sync(0xffffffffu, b3 ? a : b, 8);
    keep = kMax ? fmaxf(keep, r2) : keep + r2;
    const float r3 = __shfl_xor_sync(0xffffffffu, keep, 16);
    return kMax ? fmaxf(keep, r3) : keep + r3;
}

__device__ __forceinline__ void count_pair() {
    asm volatile("red.relaxed.gpu.global.inc.u32 [%0], %1;" ::"l"(&g_pairs_issued), "n"(kWhole / 2 * kCtas - 1) : "memory");
}
__device__ __forceinline__ void pace(uint32_t progress, int i) {
    for (int it = 0; it < 128; it++) {
        int pairs;
        asm volatile("ld.volatile.shared.u32 %0, [%1];" : "=r"(pairs) : "r"(progress) : "memory");
        if (pairs >= i * (kCtas / 2) - kPaceSlack) break;
    }
}

struct RingPos {
    int pos, slot;
    __device__ __forceinline__ void step(int n) {
        pos += n;
        slot += n;
        if (slot >= kSlots) slot -= kSlots;
    }
};

__global__ void __cluster_dims__(2, 1, 1) __launch_bounds__(kThreads, 1)
gqa_decode_kernel(const __grid_constant__ CUtensorMap map_k, const __grid_constant__ CUtensorMap map_v,
                  const __grid_constant__ CUtensorMap map_q, const __grid_constant__ CUtensorMap map_v_half,
                  __nv_bfloat16* __restrict__ out, const char* __restrict__ k_bytes) {
    asm volatile("prefetch.global.L2 [%0];" ::"l"(k_bytes + (size_t)(blockIdx.x >> 1) * (kSk * kD * 2) +
                                                   (blockIdx.x & 1) * kTileBytes + (threadIdx.x & 255) * 128) : "memory");

    extern __shared__ __align__(1024) uint8_t smem[];
    const uint32_t sb = (uint32_t)__cvta_generic_to_shared(smem);
    const int tid = threadIdx.x;
    const int head = blockIdx.x >> 1;
    const int rank = blockIdx.x & 1;
    const int group0 = head * (kSk / 8) + rank * kGroups;

    if (tid == 256) {
#pragma unroll
        for (int i = 0; i < kSlots; i++) {
            const uint32_t bar = sb + kBarFull + 8 * i;
            mbar_init(bar, (i & 1) ? 5 : 1);
            mbar_expect_tx(bar, kTileBytes + (i == 0 ? kQBytes : 0));
            tma_load(sb + kOffRing + i * kTileBytes, (i & 1) ? &map_v : &map_k, 0, group0 + (i >> 1) * 2 * kGroups, bar);
            if (i == 0) tma_load(sb + kOffQ, &map_q, 0, head * (kQRows / 8), bar);
        }
    } else if ((tid & 3) == 0 && (tid >> 2) >= kSlots && (tid >> 2) < kWhole) {
        const uint32_t bar = sb + kBarFull + 8 * (tid >> 2);
        mbar_init(bar, load_is_v(tid >> 2) ? 5 : 1);
        mbar_expect_tx(bar, kTileBytes);
    } else if (tid == 1) {
        if (sb & 1023) __trap();
#pragma unroll
        for (int i = 0; i < kSlots; i++) mbar_init(sb + kBarEmpty + 8 * i, 4);
#pragma unroll
        for (int h = 0; h < 2 * kSplit; h++) {
            mbar_init(sb + kBarHalf + 8 * h, (h & 1) ? 5 : 1);
            mbar_expect_tx(sb + kBarHalf + 8 * h, kTileBytes / 2 + ((h & 1) ? 0 : kPBytes));
        }
        asm volatile("st.shared.v2.u32 [%0], {%1, %1};" ::"r"(sb + kOffPace), "r"(0) : "memory");
        mbar_init(sb + kBarEnd, 2);
        mbar_init(sb + kBarStats, 1);
        mbar_init(sb + kBarAck, 1);
        mbar_expect_tx(sb + kBarStats, 256);
        mbar_expect_tx(sb + kBarEnd, 4096);
        asm volatile("fence.mbarrier_init.release.cluster;" ::: "memory");
    }
    __syncthreads();
    asm volatile("barrier.cluster.arrive.relaxed.aligned;" ::: "memory");

    const int lane = tid & 31, warp = (tid >> 5) & 3, t4 = lane & 3;
    const float c = 0.08838834764831845f * 1.4426950408889634f;
    const uint32_t desc_base = ((sb & 0x3FFFF) >> 4) | (1u << 16);
    uint32_t peer;
    asm("mapa.shared::cluster.u32 %0, %1, %2;" : "=r"(peer) : "r"(sb), "r"(rank ^ 1));

    if (tid >= 256) {
        if (tid == 256) {
            int slot = 0;
            uint32_t parity = 0;
#pragma unroll
            for (int i = 0; i < kSlots / 2; i++) count_pair();
#pragma unroll 1
            for (int i = kSlots; i < kWhole; i++) {
                const bool is_v = load_is_v(i);
                const int tile = i < kLoads - 2 * kEnd ? (i >> 1) : (is_v ? i - kTiles : i - (kTiles - kEnd));
                mbar_wait(sb + kBarEmpty + 8 * slot, parity);
                if (i >= kPaceFrom) pace(sb + kOffPace, i);
                tma_load(sb + kOffRing + slot * kTileBytes, is_v ? &map_v : &map_k, 0, group0 + tile * 2 * kGroups,
                         sb + kBarFull + 8 * i);
                if (i & 1) count_pair();
                if (++slot == kSlots) { slot = 0; parity ^= 1; }
            }
            asm volatile("st.volatile.shared.u32 [%0], %1;" ::"r"(sb + kOffPace + 4), "r"(1) : "memory");
#pragma unroll
            for (int h = 0; h < 2 * kSplit; h++) {
                const int pos = kWhole + (h >> 1), keys = rank ^ 1 ^ (h & 1);
                if (!(h & 1)) mbar_wait(sb + kBarEmpty + 8 * (pos % kSlots), (pos / kSlots - 1) & 1);
                if (h == 2) mbar_wait(sb + kBarHalf + 8, 0);
                tma_load(sb + kOffRing + (pos % kSlots) * kTileBytes + keys * (kTileBytes / 2), &map_v_half, rank,
                         head * (kSk / 8) + ((pos - kTiles) * 2 + keys) * kGroups, sb + kBarHalf + 8 * h);
            }
        } else if (tid == 288) {
            for (int it = 0; it < 4096; it++) {
                uint32_t pairs, done;
                asm volatile("ld.relaxed.gpu.global.u32 %0, [%1];" : "=r"(pairs) : "l"(&g_pairs_issued) : "memory");
                asm volatile("st.volatile.shared.u32 [%0], %1;" ::"r"(sb + kOffPace), "r"(pairs) : "memory");
                asm volatile("ld.volatile.shared.u32 %0, [%1];" : "=r"(done) : "r"(sb + kOffPace + 4) : "memory");
                if (done) break;
            }
        }
    } else if (tid < 128) {
        const int my_col = 2 * t4 + ((lane >> 3) & 1) + 8 * ((lane >> 2) & 1);
        const uint32_t red_wr = sb + kOffRed + (my_col * 4 + warp) * 4;
        const uint32_t red_rd = sb + kOffRed + (2 * t4) * 16;
        const uint32_t dq = uniform(desc_base + (kOffQ >> 4));
        float s[2][8], m[4], l[4], a[4], a_prev[4];
#pragma unroll
        for (int j = 0; j < 4; j++) { m[j] = -INFINITY; l[j] = 0.f; a[j] = 0.f; }
        RingPos kc{0, 0};
        int pb = 0;
        asm volatile("barrier.cluster.wait.aligned;" ::: "memory");

#pragma unroll 1
        for (int t = 0; t < kTiles; t++) {
            const uint32_t dk = uniform(desc_base + kc.slot * (kTileBytes >> 4));
            mbar_wait(sb + kBarFull + 8 * kc.pos, 0);
            pin(s[0]); pin(s[1]);
            wg_fence();
#pragma unroll
            for (int k = 0; k < kD / 16; k++) {
                const uint32_t off = ((k >> 2) * 1024 + (k & 3) * 32) >> 4;
#pragma unroll
                for (int mt = 0; mt < 2; mt++) {
                    if (k == 0) wgmma<0, 0, kHiTile, kHiTile>(s[mt], dk + off + mt * (16384 >> 4), dq + off);
                    else        wgmma<1, 0, kHiTile, kHiTile>(s[mt], dk + off + mt * (16384 >> 4), dq + off);
                }
            }
            wg_commit();
            wg_wait<0>();
            pin(s[0]); pin(s[1]);
            if (lane == 0) mbar_arrive(sb + kBarEmpty + 8 * kc.slot);
            kc.step(t < kTiles - kEnd ? 2 : 1);

            float x[4];
#pragma unroll
            for (int j = 0; j < 4; j++) {
                const int i0 = (j >> 1) * 4 + (j & 1);
                x[j] = fmaxf(fmaxf(s[0][i0], s[0][i0 + 2]), fmaxf(s[1][i0], s[1][i0 + 2]));
            }
            const float wmax = warp_col_reduce<true>(x, lane);
            const uint32_t rb = (t & 1) * 256;
            if (lane < 16) sts32(red_wr + rb, wmax);
            score_group_sync();
            float mc[4];
#pragma unroll
            for (int j = 0; j < 4; j++) {
                float r[4];
                lds128(r, red_rd + rb + ((j >> 1) * 8 + (j & 1)) * 16);
                const float mn = fmaxf(fmaxf(fmaxf(r[0], r[1]), fmaxf(r[2], r[3])), m[j]);
                a_prev[j] = a[j];
                a[j] = ex2((m[j] - mn) * c);
                m[j] = mn;
                mc[j] = mn * c;
                l[j] *= a[j];
            }
            const uint32_t p_buf = sb + kOffP + pb * kPStride;
#pragma unroll
            for (int mt = 0; mt < 2; mt++) {
                float p[8];
#pragma unroll
                for (int i = 0; i < 8; i++) {
                    p[i] = ex2(fmaf(s[mt][i], c, -mc[col(i)]));
                    l[col(i)] += p[i];
                }
                asm volatile("stmatrix.sync.aligned.m8n8.x4.trans.shared.b16 [%0], {%1, %2, %3, %4};"
                             ::"r"(p_buf + mt * 2048 + warp * 512 + lane * 16), "r"(pack_bf16(p[0], p[1])),
                               "r"(pack_bf16(p[2], p[3])), "r"(pack_bf16(p[4], p[5])), "r"(pack_bf16(p[6], p[7]))
                             : "memory");
            }
            if (tid < 4) sts128(p_buf + kPBytes + tid * 16, a);
            asm volatile("fence.proxy.async.shared::cta;" ::: "memory");
            __syncwarp();
            if (lane == 0) {
                if (t < kTiles - kSplit) {
                    mbar_arrive(sb + kBarFull + 8 * (t < kTiles - kEnd ? 2 * t + 1 : t + kTiles));
                } else {
                    const int u = t - (kTiles - kSplit);
                    const uint32_t dst = peer + kOffPeerP + u * kPBytes + warp * 512;
                    mbar_arrive(sb + kBarHalf + 16 * u + 8);
                    copy_to_peer(dst, p_buf + warp * 512, 512, peer + kBarHalf + 16 * u);
                    copy_to_peer(dst + 2048, p_buf + warp * 512 + 2048, 512, peer + kBarHalf + 16 * u);
                }
            }
            if (++pb == kEnd) pb = 0;
        }

        const float wsum = warp_col_reduce<false>(l, lane);
        if (lane < 16) sts32(red_wr + 512, wsum);
        score_group_sync();
        if (warp == 0) {
#pragma unroll
            for (int j = 0; j < 4; j++) {
                float r[4];
                lds128(r, red_rd + 512 + ((j >> 1) * 8 + (j & 1)) * 16);
                l[j] = (r[0] + r[1]) + (r[2] + r[3]);
            }
            if (tid < 4) {
                st_async_v4(peer + kOffPeerStats + tid * 16, m, peer + kBarStats);
                st_async_v4(peer + kOffPeerStats + 64 + tid * 16, l, peer + kBarStats);
                st_async_v4(peer + kOffPeerStats + 128 + tid * 16, a, peer + kBarStats);
                st_async_v4(peer + kOffPeerStats + 192 + tid * 16, a_prev, peer + kBarStats);
            }
            mbar_wait_peer(sb + kBarStats);
            float pm[4], pl[4], pa[4], pa_prev[4], coef[6][4];
            lds128(pm, sb + kOffPeerStats + t4 * 16);
            lds128(pl, sb + kOffPeerStats + 64 + t4 * 16);
            lds128(pa, sb + kOffPeerStats + 128 + t4 * 16);
            lds128(pa_prev, sb + kOffPeerStats + 192 + t4 * 16);
#pragma unroll
            for (int j = 0; j < 4; j++) {
                const float mt = fmaxf(m[j], pm[j]);
                const float eo = ex2((m[j] - mt) * c), ep = ex2((pm[j] - mt) * c);
                const float inv = 1.f / (eo * l[j] + ep * pl[j]);
                coef[0][j] = eo * inv;
                coef[1][j] = ep * inv;
                coef[2][j] = coef[0][j] * a[j];
                coef[3][j] = coef[1][j] * pa[j];
                coef[4][j] = coef[2][j] * a_prev[j];
                coef[5][j] = coef[3][j] * pa_prev[j];
            }
            if (tid < 4) {
#pragma unroll
                for (int q = 0; q < 6; q++) sts128(sb + kOffCoef + q * 64 + tid * 16, coef[q]);
            }
            __syncwarp();
            if (lane == 0) mbar_arrive(sb + kBarEnd);
            mbar_wait(sb + kBarAck, 0);
        }
    } else {
        float o[2][8], T[2][2][8], alpha[2][4];
#pragma unroll
        for (int i = 0; i < 8; i++) o[0][i] = o[1][i] = 0.f;
        const int wt = tid - 128;
        const uint32_t dv0 = uniform(desc_base + rank * (1024 >> 4));
        const uint32_t dv1 = dv0 + (1024 >> 4) - rank * (2048 >> 4);
        const uint32_t dp = uniform((((sb + kOffP) & 0x3FFFF) >> 4) | ((128 >> 4) << 16));
        asm volatile("barrier.cluster.wait.aligned;" ::: "memory");

        RingPos vc{1, 1};
        int pb = 0;
#pragma unroll 1
        for (int t = 0; t < kTiles - kEnd; t++) {
            const uint32_t va = uniform(vc.slot * (kTileBytes >> 4)), pa = uniform(dp + pb * (kPStride >> 4));
            mbar_wait(sb + kBarFull + 8 * vc.pos, 0);
            lds128(alpha[0], sb + kOffP + pb * kPStride + kPBytes + t4 * 16);
            pin(T[0][0]); pin(T[0][1]);
            issue_pv(T[0], dv0 + va, dv1 + va, pa);
            wg_wait<0>();
            if (lane == 0) mbar_arrive(sb + kBarEmpty + 8 * vc.slot);
            fold(o[1], T[0][1], alpha[0]);
            fold(o[0], T[0][0], alpha[0]);
            vc.step(2);
            if (++pb == kEnd) pb = 0;
        }

#pragma unroll
        for (int j = 0; j < kEnd - kSplit; j++) {
            const int t = kTiles - kEnd + j, pos = kLoads - kEnd + j, slot = pos % kSlots;
            float (&d)[2][8] = T[j & 1];
            float (&prev)[2][8] = T[(j + 1) & 1];
            pin(d[0]); pin(d[1]);
            mbar_wait(sb + kBarFull + 8 * pos, 0);
            lds128(alpha[j & 1], sb + kOffP + (t % kEnd) * kPStride + kPBytes + t4 * 16);
            issue_pv(d, dv0 + slot * (kTileBytes >> 4), dv1 + slot * (kTileBytes >> 4), dp + (t % kEnd) * (kPStride >> 4));
            if (pos + kSlots < kLoads) {
                wg_wait<0>();
                if (lane == 0) mbar_arrive(sb + kBarEmpty + 8 * slot);
            }
            if (j > 0) {
                wg_wait<1>();
                fold(o[1], prev[1], alpha[(j + 1) & 1]);
                fold(o[0], prev[0], alpha[(j + 1) & 1]);
            }
            if (j == kEnd - kSplit - 1) {
                wg_wait<0>();
                fold(o[1], d[1], alpha[j & 1]);
                st_async_v4(peer + kOffPeerO + wt * 16, &o[1][0], peer + kBarEnd);
                st_async_v4(peer + kOffPeerO + 2048 + wt * 16, &o[1][4], peer + kBarEnd);
                fold(o[0], d[0], alpha[j & 1]);
            }
        }

        const uint32_t dh_own = uniform(desc_base + rank * (16384 >> 4));
        const uint32_t dh_peer = dh_own + (16384 >> 4) - rank * (32768 >> 4);
        float coef[6][4], r[8];
#pragma unroll
        for (int h = 0; h < 2 * kSplit; h++) {
            const int u = h >> 1;
            const uint32_t va = ((kWhole + u) % kSlots) * (kTileBytes >> 4);
            float (&d)[8] = T[u][h & 1];
            pin(d);
            if (h & 1) {
                mbar_wait(sb + kBarHalf + 8 * h, 0);
                issue_pv_half(d, dh_own + va, dp + ((kTiles - kSplit + u) % kEnd) * (kPStride >> 4));
            } else {
                mbar_wait_peer(sb + kBarHalf + 8 * h);
                issue_pv_half(d, dh_peer + va, dp - ((kOffP - kOffPeerP) >> 4) + u * (kPBytes >> 4));
            }
            if (h == 2 * kSplit - 2 && wt == 0)
                asm volatile("mbarrier.arrive.relaxed.cluster.shared::cluster.b64 _, [%0];" ::"r"(peer + kBarAck) : "memory");
            if (h == 1) {
                mbar_wait_peer(sb + kBarEnd);
#pragma unroll
                for (int q = 0; q < 6; q++) lds128(coef[q], sb + kOffCoef + q * 64 + t4 * 16);
                float px[8];
                lds128(&px[0], sb + kOffPeerO + wt * 16);
                lds128(&px[4], sb + kOffPeerO + 2048 + wt * 16);
#pragma unroll
                for (int i = 0; i < 8; i++) r[i] = fmaf(o[0][i], coef[4][col(i)], px[i] * coef[5][col(i)]);
            }
            if (h > 0) {
                float (&e)[8] = T[(h - 1) >> 1][(h - 1) & 1];
                wg_wait<1>();
                pin(e);
#pragma unroll
                for (int i = 0; i < 8; i++) r[i] = fmaf(e[i], coef[2 * kSplit - h][col(i)], r[i]);
            }
        }
        wg_wait<0>();
        pin(T[kSplit - 1][1]);
#pragma unroll
        for (int i = 0; i < 8; i++) r[i] = fmaf(T[kSplit - 1][1][i], coef[0][col(i)], r[i]);

        uint32_t* dst = reinterpret_cast<uint32_t*>(out + (head * kQRows + (lane >> 2)) * kD + rank * 64 + warp * 16 + 2 * t4);
#pragma unroll
        for (int b = 0; b < 4; b++) {
            uint32_t tr;
            asm volatile("movmatrix.sync.aligned.m8n8.trans.b16 %0, %1;" : "=r"(tr) : "r"(pack_bf16(r[2 * b], r[2 * b + 1])));
            dst[(b >> 1) * (8 * kD / 2) + (b & 1) * 4] = tr;
        }
    }
}

using EncodeFn = CUresult (*)(CUtensorMap*, CUtensorMapDataType, cuuint32_t, void*, const cuuint64_t*,
                              const cuuint64_t*, const cuuint32_t*, const cuuint32_t*, CUtensorMapInterleave,
                              CUtensorMapSwizzle, CUtensorMapL2promotion, CUtensorMapFloatOOBfill);

CUtensorMap make_map(EncodeFn encode, void* ptr, uint64_t rows, uint32_t box_halves, uint32_t box_rows) {
    CUtensorMap map;
    const cuuint64_t dims[4] = {64, 8, 2, rows / 8};
    const cuuint64_t strides[3] = {256, 128, 2048};
    const cuuint32_t box[4] = {64, 8, box_halves, box_rows / 8};
    const cuuint32_t elem[4] = {1, 1, 1, 1};
    encode(&map, CU_TENSOR_MAP_DATA_TYPE_BFLOAT16, 4, ptr, dims, strides, box, elem, CU_TENSOR_MAP_INTERLEAVE_NONE,
           CU_TENSOR_MAP_SWIZZLE_128B, CU_TENSOR_MAP_L2_PROMOTION_NONE, CU_TENSOR_MAP_FLOAT_OOB_FILL_NONE);
    return map;
}

}

extern "C" void kernel_launch(void* const* d_in, const int* in_sizes, int n_in, void* d_out, int out_size) {
    (void)in_sizes; (void)n_in; (void)out_size;
    static EncodeFn encode = nullptr;
    if (!encode) {
        cudaDriverEntryPointQueryResult status;
        cudaGetDriverEntryPoint("cuTensorMapEncodeTiled", reinterpret_cast<void**>(&encode), cudaEnableDefault, &status);
        cudaFuncSetAttribute(gqa_decode_kernel, cudaFuncAttributeMaxDynamicSharedMemorySize, kSmemBytes);
    }
    const uint64_t kv_rows = (uint64_t)kHeads * kSk;
    const CUtensorMap map_q = make_map(encode, d_in[0], (uint64_t)kHeads * kQRows, 2, kQRows);
    const CUtensorMap map_k = make_map(encode, d_in[1], kv_rows, 2, kTile);
    const CUtensorMap map_v = make_map(encode, d_in[2], kv_rows, 2, kTile);
    const CUtensorMap map_v_half = make_map(encode, d_in[2], kv_rows, 1, kTile);
    gqa_decode_kernel<<<kCtas, kThreads, kSmemBytes>>>(map_k, map_v, map_q, map_v_half,
                                                       static_cast<__nv_bfloat16*>(d_out),
                                                       static_cast<const char*>(d_in[1]));
}
```

```cpp
#include <cuda_runtime.h>
#include <cuda_bf16.h>
#include <cuda.h>
#include <stdint.h>

namespace {

constexpr int kD = 128;
constexpr int kSk = 8192;
constexpr int kHeads = 64;
constexpr int kQRows = 16;
constexpr int kTile = 128;
constexpr int kTiles = kSk / 2 / kTile;
constexpr int kLoads = 2 * kTiles;
constexpr int kSlots = 5;
constexpr int kEnd = 6;
constexpr int kSplit = 2;
constexpr int kWhole = kLoads - kSplit;
constexpr int kGroups = kTile / 8;
constexpr int kThreads = 320;
constexpr int kCtas = 2 * kHeads;
constexpr int kPaceFrom = 8;
constexpr int kPaceSlack = 72;

constexpr uint32_t kTileBytes = kTile * kD * 2;
constexpr uint32_t kQBytes = kQRows * kD * 2;
constexpr uint32_t kPBytes = kTile * kQRows * 2;
constexpr uint32_t kPStride = kPBytes + 64;

constexpr uint32_t kOffRing = 0;
constexpr uint32_t kOffQ = kOffRing + kSlots * kTileBytes;
constexpr uint32_t kOffPeerO = kOffQ + kQBytes;
constexpr uint32_t kOffPeerP = kOffPeerO + 4096;
constexpr uint32_t kOffP = kOffPeerP + kSplit * kPBytes;
constexpr uint32_t kOffPeerStats = kOffP + kEnd * kPStride;
constexpr uint32_t kOffRed = kOffPeerStats + 256;
constexpr uint32_t kOffCoef = kOffRed + 768;
constexpr uint32_t kBarFull = kOffCoef + 384;
constexpr uint32_t kBarHalf = kBarFull + 8 * kWhole;
constexpr uint32_t kBarEmpty = kBarHalf + 8 * 2 * kSplit;
constexpr uint32_t kBarEnd = kBarEmpty + 8 * kSlots;
constexpr uint32_t kBarStats = kBarEnd + 8;
constexpr uint32_t kBarAck = kBarStats + 8;
constexpr uint32_t kOffPace = kBarAck + 8;
constexpr uint32_t kSmemBytes = kOffPace + 8;

static_assert(kSplit == 2 && kEnd >= kSlots && kEnd - kSlots < kEnd - kSplit, "tail schedule");
static_assert(kTiles == 32, "the tile swizzle permutes 32 steps");
static_assert(kPaceSlack >= kCtas / 2 && kWhole % 2 == 0, "the slowest CTA is never held back");

constexpr uint64_t kEvictFirst = 0x12F0000000000000ull;
constexpr int kSpinLimit = 1 << 24;

constexpr uint32_t kHiTile = (2048 >> 4) | (1u << 30);
constexpr uint32_t kHiHalf = (1024 >> 4) | (1u << 30);
constexpr uint32_t kHiP = 256 >> 4;

__device__ unsigned g_pairs_issued;

__device__ __forceinline__ int step_group(int head, int t) {
    const int swizzle = ((head & 1) ? 26 : 0) ^ ((head & 2) ? 20 : 0);
    return head * (kSk / 8) + (t ^ swizzle) * 2 * kGroups;
}

__device__ __forceinline__ bool load_is_v(int i) { return i < kLoads - 2 * kEnd ? (i & 1) : i >= kLoads - kEnd; }

__device__ __forceinline__ void mbar_init(uint32_t bar, uint32_t count) {
    asm volatile("mbarrier.init.shared::cta.b64 [%0], %1;" ::"r"(bar), "r"(count) : "memory");
}
__device__ __forceinline__ void mbar_expect_tx(uint32_t bar, uint32_t bytes) {
    asm volatile("mbarrier.arrive.expect_tx.shared::cta.b64 _, [%0], %1;" ::"r"(bar), "r"(bytes) : "memory");
}
__device__ __forceinline__ void mbar_arrive(uint32_t bar) {
    asm volatile("mbarrier.arrive.shared::cta.b64 _, [%0];" ::"r"(bar) : "memory");
}
__device__ __forceinline__ void mbar_wait(uint32_t bar, uint32_t parity) {
    asm volatile(
        "{\n.reg .pred p;\n.reg .u32 n;\nmov.u32 n, 0;\n"
        "WAIT_LOOP:\n"
        "mbarrier.try_wait.parity.shared::cta.b64 p, [%0], %1;\n"
        "@p bra WAIT_DONE;\n"
        "add.u32 n, n, 1;\nsetp.lt.u32 p, n, %2;\n@p bra WAIT_LOOP;\ntrap;\n"
        "WAIT_DONE:\n}"
        ::"r"(bar), "r"(parity), "n"(kSpinLimit) : "memory");
}
__device__ __forceinline__ void mbar_wait_peer(uint32_t bar) {
    mbar_wait(bar, 0);
    asm volatile("fence.acquire.sync_restrict::shared::cluster.cluster;" ::: "memory");
}
__device__ __forceinline__ void tma_load(uint32_t dst, const CUtensorMap* map, int half, int group, uint32_t bar) {
    asm volatile(
        "cp.async.bulk.tensor.4d.shared::cluster.global.mbarrier::complete_tx::bytes.L2::cache_hint "
        "[%0], [%1, {%3, %3, %4, %5}], [%2], %6;"
        ::"r"(dst), "l"(map), "r"(bar), "r"(0), "r"(half), "r"(group), "l"(kEvictFirst) : "memory");
}
__device__ __forceinline__ void copy_to_peer(uint32_t dst, uint32_t src, uint32_t bytes, uint32_t bar) {
    asm volatile("cp.async.bulk.shared::cluster.shared::cta.mbarrier::complete_tx::bytes [%0], [%1], %2, [%3];"
                 ::"r"(dst), "r"(src), "r"(bytes), "r"(bar) : "memory");
}
__device__ __forceinline__ void st_async_v4(uint32_t dst, const float* v, uint32_t bar) {
    asm volatile("st.async.weak.shared::cluster.mbarrier::complete_tx::bytes.v4.f32 [%0], {%1, %2, %3, %4}, [%5];"
                 ::"r"(dst), "f"(v[0]), "f"(v[1]), "f"(v[2]), "f"(v[3]), "r"(bar) : "memory");
}
__device__ __forceinline__ void lds128(float* v, uint32_t addr) {
    asm volatile("ld.shared.v4.f32 {%0, %1, %2, %3}, [%4];"
                 : "=f"(v[0]), "=f"(v[1]), "=f"(v[2]), "=f"(v[3]) : "r"(addr) : "memory");
}
__device__ __forceinline__ void sts128(uint32_t addr, const float* v) {
    asm volatile("st.shared.v4.f32 [%0], {%1, %2, %3, %4};"
                 ::"r"(addr), "f"(v[0]), "f"(v[1]), "f"(v[2]), "f"(v[3]) : "memory");
}
__device__ __forceinline__ void sts32(uint32_t addr, float v) {
    asm volatile("st.shared.f32 [%0], %1;" ::"r"(addr), "f"(v) : "memory");
}
__device__ __forceinline__ void score_group_sync() { asm volatile("bar.sync 1, 128;" ::: "memory"); }
__device__ __forceinline__ float ex2(float x) {
    float y;
    asm("ex2.approx.ftz.f32 %0, %1;" : "=f"(y) : "f"(x));
    return y;
}
__device__ __forceinline__ uint32_t pack_bf16(float lo, float hi) {
    uint32_t r;
    asm("cvt.rn.bf16x2.f32 %0, %1, %2;" : "=r"(r) : "f"(hi), "f"(lo));
    return r;
}
__device__ __forceinline__ uint32_t uniform(uint32_t x) { return __shfl_sync(0xffffffffu, x, 0); }

__device__ __forceinline__ void wg_fence() { asm volatile("wgmma.fence.sync.aligned;" ::: "memory"); }
__device__ __forceinline__ void wg_commit() { asm volatile("wgmma.commit_group.sync.aligned;" ::: "memory"); }
template <int N>
__device__ __forceinline__ void wg_wait() { asm volatile("wgmma.wait_group.sync.aligned %0;" ::"n"(N) : "memory"); }

template <int kAccumulate, int kTransA, uint32_t kHiA, uint32_t kHiB>
__device__ __forceinline__ void wgmma(float (&d)[8], uint32_t lo_a, uint32_t lo_b) {
    asm volatile(
        "{\n.reg .b64 da, db;\nmov.b64 da, {%8, %12};\nmov.b64 db, {%9, %13};\n"
        "wgmma.mma_async.sync.aligned.m64n16k16.f32.bf16.bf16 "
        "{%0, %1, %2, %3, %4, %5, %6, %7}, da, db, %10, 1, 1, %11, 0;\n}"
        : "+f"(d[0]), "+f"(d[1]), "+f"(d[2]), "+f"(d[3]), "+f"(d[4]), "+f"(d[5]), "+f"(d[6]), "+f"(d[7])
        : "r"(lo_a), "r"(lo_b), "n"(kAccumulate), "n"(kTransA), "n"(kHiA), "n"(kHiB));
}
__device__ __forceinline__ void pin(float (&d)[8]) {
    asm volatile("" : "+f"(d[0]), "+f"(d[1]), "+f"(d[2]), "+f"(d[3]), "+f"(d[4]), "+f"(d[5]), "+f"(d[6]), "+f"(d[7])::"memory");
}

__device__ __forceinline__ void issue_pv(float (&d)[2][8], uint32_t a0, uint32_t a1, uint32_t p) {
    wg_fence();
    wgmma<0, 1, kHiTile, kHiP>(d[1], a1, p);
    wgmma<0, 1, kHiTile, kHiP>(d[0], a0, p);
#pragma unroll
    for (int k = 1; k < kTile / 16; k++) {
        wgmma<1, 1, kHiTile, kHiP>(d[1], a1 + k * (4096 >> 4), p + k * (512 >> 4));
        wgmma<1, 1, kHiTile, kHiP>(d[0], a0 + k * (4096 >> 4), p + k * (512 >> 4));
    }
    wg_commit();
}
__device__ __forceinline__ void issue_pv_half(float (&d)[8], uint32_t a, uint32_t p) {
    wg_fence();
    wgmma<0, 1, kHiHalf, kHiP>(d, a, p);
#pragma unroll
    for (int k = 1; k < kTile / 16; k++) wgmma<1, 1, kHiHalf, kHiP>(d, a + k * (2048 >> 4), p + k * (512 >> 4));
    wg_commit();
}

__device__ __forceinline__ constexpr int col(int i) { return (i >> 2) * 2 + (i & 1); }

__device__ __forceinline__ void fold(float (&acc)[8], float (&d)[8], const float (&a)[4]) {
    pin(d);
#pragma unroll
    for (int i = 0; i < 8; i++) acc[i] = fmaf(acc[i], a[col(i)], d[i]);
}

template <bool kMax>
__device__ __forceinline__ float warp_col_reduce(const float (&x)[4], int lane) {
    const bool b2 = lane & 4, b3 = lane & 8;
    float a = b2 ? x[2] : x[0], b = b2 ? x[3] : x[1];
    const float ra = __shfl_xor_sync(0xffffffffu, b2 ? x[0] : x[2], 4);
    const float rb = __shfl_xor_sync(0xffffffffu, b2 ? x[1] : x[3], 4);
    a = kMax ? fmaxf(a, ra) : a + ra;
    b = kMax ? fmaxf(b, rb) : b + rb;
    float keep = b3 ? b : a;
    const float r2 = __shfl_xor_sync(0xffffffffu, b3 ? a : b, 8);
    keep = kMax ? fmaxf(keep, r2) : keep + r2;
    const float r3 = __shfl_xor_sync(0xffffffffu, keep, 16);
    return kMax ? fmaxf(keep, r3) : keep + r3;
}

__device__ __forceinline__ void count_pair() {
    asm volatile("red.relaxed.gpu.global.inc.u32 [%0], %1;" ::"l"(&g_pairs_issued), "n"(kWhole / 2 * kCtas - 1) : "memory");
}
__device__ __forceinline__ void pace(uint32_t progress, int i) {
    for (int it = 0; it < 128; it++) {
        int pairs;
        asm volatile("ld.volatile.shared.u32 %0, [%1];" : "=r"(pairs) : "r"(progress) : "memory");
        if (pairs >= i * (kCtas / 2) - kPaceSlack) break;
    }
}

struct RingPos {
    int pos, slot;
    __device__ __forceinline__ void step(int n) {
        pos += n;
        slot += n;
        if (slot >= kSlots) slot -= kSlots;
    }
};

__global__ void __cluster_dims__(2, 1, 1) __launch_bounds__(kThreads, 1)
gqa_decode_kernel(const __grid_constant__ CUtensorMap map_k, const __grid_constant__ CUtensorMap map_v,
                  const __grid_constant__ CUtensorMap map_q, const __grid_constant__ CUtensorMap map_v_half,
                  __nv_bfloat16* __restrict__ out, const char* __restrict__ k_bytes) {
    const int tid = threadIdx.x;
    const int head = blockIdx.x >> 1;
    const int rank = blockIdx.x & 1;

    asm volatile("prefetch.global.L2 [%0];"
                 ::"l"(k_bytes + (size_t)(step_group(head, 0) + rank * kGroups) * 2048 + (tid & 255) * 128) : "memory");

    extern __shared__ __align__(1024) uint8_t smem[];
    const uint32_t sb = (uint32_t)__cvta_generic_to_shared(smem);

    if (tid == 256) {
#pragma unroll
        for (int i = 0; i < kSlots; i++) {
            const uint32_t bar = sb + kBarFull + 8 * i;
            mbar_init(bar, (i & 1) ? 5 : 1);
            mbar_expect_tx(bar, kTileBytes + (i == 0 ? kQBytes : 0));
            tma_load(sb + kOffRing + i * kTileBytes, (i & 1) ? &map_v : &map_k, 0,
                     step_group(head, i >> 1) + rank * kGroups, bar);
            if (i == 0) tma_load(sb + kOffQ, &map_q, 0, head * (kQRows / 8), bar);
        }
    } else if ((tid & 3) == 0 && (tid >> 2) >= kSlots && (tid >> 2) < kWhole) {
        const uint32_t bar = sb + kBarFull + 8 * (tid >> 2);
        mbar_init(bar, load_is_v(tid >> 2) ? 5 : 1);
        mbar_expect_tx(bar, kTileBytes);
    } else if (tid == 1) {
        if (sb & 1023) __trap();
#pragma unroll
        for (int i = 0; i < kSlots; i++) mbar_init(sb + kBarEmpty + 8 * i, 4);
#pragma unroll
        for (int h = 0; h < 2 * kSplit; h++) {
            mbar_init(sb + kBarHalf + 8 * h, (h & 1) ? 5 : 1);
            mbar_expect_tx(sb + kBarHalf + 8 * h, kTileBytes / 2 + ((h & 1) ? 0 : kPBytes));
        }
        asm volatile("st.shared.v2.u32 [%0], {%1, %1};" ::"r"(sb + kOffPace), "r"(0) : "memory");
        mbar_init(sb + kBarEnd, 2);
        mbar_init(sb + kBarStats, 1);
        mbar_init(sb + kBarAck, 1);
        mbar_expect_tx(sb + kBarStats, 256);
        mbar_expect_tx(sb + kBarEnd, 4096);
        asm volatile("fence.mbarrier_init.release.cluster;" ::: "memory");
    }
    __syncthreads();
    asm volatile("barrier.cluster.arrive.relaxed.aligned;" ::: "memory");

    const int lane = tid & 31, warp = (tid >> 5) & 3, t4 = lane & 3;
    const float c = 0.08838834764831845f * 1.4426950408889634f;
    const uint32_t desc_base = ((sb & 0x3FFFF) >> 4) | (1u << 16);
    uint32_t peer;
    asm("mapa.shared::cluster.u32 %0, %1, %2;" : "=r"(peer) : "r"(sb), "r"(rank ^ 1));

    if (tid >= 256) {
        if (tid == 256) {
            int slot = 0;
            uint32_t parity = 0;
#pragma unroll
            for (int i = 0; i < kSlots / 2; i++) count_pair();
#pragma unroll 1
            for (int i = kSlots; i < kWhole; i++) {
                const bool is_v = load_is_v(i);
                const int tile = i < kLoads - 2 * kEnd ? (i >> 1) : (is_v ? i - kTiles : i - (kTiles - kEnd));
                mbar_wait(sb + kBarEmpty + 8 * slot, parity);
                if (i >= kPaceFrom) pace(sb + kOffPace, i);
                tma_load(sb + kOffRing + slot * kTileBytes, is_v ? &map_v : &map_k, 0,
                         step_group(head, tile) + rank * kGroups, sb + kBarFull + 8 * i);
                if (i & 1) count_pair();
                if (++slot == kSlots) { slot = 0; parity ^= 1; }
            }
            asm volatile("st.volatile.shared.u32 [%0], %1;" ::"r"(sb + kOffPace + 4), "r"(1) : "memory");
#pragma unroll
            for (int h = 0; h < 2 * kSplit; h++) {
                const int pos = kWhole + (h >> 1), keys = rank ^ 1 ^ (h & 1);
                if (!(h & 1)) mbar_wait(sb + kBarEmpty + 8 * (pos % kSlots), (pos / kSlots - 1) & 1);
                if (h == 2) mbar_wait(sb + kBarHalf + 8, 0);
                tma_load(sb + kOffRing + (pos % kSlots) * kTileBytes + keys * (kTileBytes / 2), &map_v_half, rank,
                         step_group(head, pos - kTiles) + keys * kGroups, sb + kBarHalf + 8 * h);
            }
        } else if (tid == 288) {
            for (int it = 0; it < 4096; it++) {
                uint32_t pairs, done;
                asm volatile("ld.relaxed.gpu.global.u32 %0, [%1];" : "=r"(pairs) : "l"(&g_pairs_issued) : "memory");
                asm volatile("st.volatile.shared.u32 [%0], %1;" ::"r"(sb + kOffPace), "r"(pairs) : "memory");
                asm volatile("ld.volatile.shared.u32 %0, [%1];" : "=r"(done) : "r"(sb + kOffPace + 4) : "memory");
                if (done) break;
            }
        }
    } else if (tid < 128) {
        const int my_col = 2 * t4 + ((lane >> 3) & 1) + 8 * ((lane >> 2) & 1);
        const uint32_t red_wr = sb + kOffRed + (my_col * 4 + warp) * 4;
        const uint32_t red_rd = sb + kOffRed + (2 * t4) * 16;
        const uint32_t dq = uniform(desc_base + (kOffQ >> 4));
        float s[2][8], m[4], l[4], a[4], a_prev[4];
#pragma unroll
        for (int j = 0; j < 4; j++) { m[j] = -INFINITY; l[j] = 0.f; a[j] = 0.f; }
        RingPos kc{0, 0};
        int pb = 0;
        asm volatile("barrier.cluster.wait.aligned;" ::: "memory");

#pragma unroll 1
        for (int t = 0; t < kTiles; t++) {
            const uint32_t dk = uniform(desc_base + kc.slot * (kTileBytes >> 4));
            mbar_wait(sb + kBarFull + 8 * kc.pos, 0);
            pin(s[0]); pin(s[1]);
            wg_fence();
#pragma unroll
            for (int k = 0; k < kD / 16; k++) {
                const uint32_t off = ((k >> 2) * 1024 + (k & 3) * 32) >> 4;
#pragma unroll
                for (int mt = 0; mt < 2; mt++) {
                    if (k == 0) wgmma<0, 0, kHiTile, kHiTile>(s[mt], dk + off + mt * (16384 >> 4), dq + off);
                    else        wgmma<1, 0, kHiTile, kHiTile>(s[mt], dk + off + mt * (16384 >> 4), dq + off);
                }
            }
            wg_commit();
            wg_wait<0>();
            pin(s[0]); pin(s[1]);
            if (lane == 0) mbar_arrive(sb + kBarEmpty + 8 * kc.slot);
            kc.step(t < kTiles - kEnd ? 2 : 1);

            float x[4];
#pragma unroll
            for (int j = 0; j < 4; j++) {
                const int i0 = (j >> 1) * 4 + (j & 1);
                x[j] = fmaxf(fmaxf(s[0][i0], s[0][i0 + 2]), fmaxf(s[1][i0], s[1][i0 + 2]));
            }
            const float wmax = warp_col_reduce<true>(x, lane);
            const uint32_t rb = (t & 1) * 256;
            if (lane < 16) sts32(red_wr + rb, wmax);
            score_group_sync();
            float mc[4];
#pragma unroll
            for (int j = 0; j < 4; j++) {
                float r[4];
                lds128(r, red_rd + rb + ((j >> 1) * 8 + (j & 1)) * 16);
                const float mn = fmaxf(fmaxf(fmaxf(r[0], r[1]), fmaxf(r[2], r[3])), m[j]);
                a_prev[j] = a[j];
                a[j] = ex2((m[j] - mn) * c);
                m[j] = mn;
                mc[j] = mn * c;
                l[j] *= a[j];
            }
            const uint32_t p_buf = sb + kOffP + pb * kPStride;
#pragma unroll
            for (int mt = 0; mt < 2; mt++) {
                float p[8];
#pragma unroll
                for (int i = 0; i < 8; i++) {
                    p[i] = ex2(fmaf(s[mt][i], c, -mc[col(i)]));
                    l[col(i)] += p[i];
                }
                asm volatile("stmatrix.sync.aligned.m8n8.x4.trans.shared.b16 [%0], {%1, %2, %3, %4};"
                             ::"r"(p_buf + mt * 2048 + warp * 512 + lane * 16), "r"(pack_bf16(p[0], p[1])),
                               "r"(pack_bf16(p[2], p[3])), "r"(pack_bf16(p[4], p[5])), "r"(pack_bf16(p[6], p[7]))
                             : "memory");
            }
            if (tid < 4) sts128(p_buf + kPBytes + tid * 16, a);
            asm volatile("fence.proxy.async.shared::cta;" ::: "memory");
            __syncwarp();
            if (lane == 0) {
                if (t < kTiles - kSplit) {
                    mbar_arrive(sb + kBarFull + 8 * (t < kTiles - kEnd ? 2 * t + 1 : t + kTiles));
                } else {
                    const int u = t - (kTiles - kSplit);
                    const uint32_t dst = peer + kOffPeerP + u * kPBytes + warp * 512;
                    mbar_arrive(sb + kBarHalf + 16 * u + 8);
                    copy_to_peer(dst, p_buf + warp * 512, 512, peer + kBarHalf + 16 * u);
                    copy_to_peer(dst + 2048, p_buf + warp * 512 + 2048, 512, peer + kBarHalf + 16 * u);
                }
            }
            if (++pb == kEnd) pb = 0;
        }

        const float wsum = warp_col_reduce<false>(l, lane);
        if (lane < 16) sts32(red_wr + 512, wsum);
        score_group_sync();
        if (warp == 0) {
#pragma unroll
            for (int j = 0; j < 4; j++) {
                float r[4];
                lds128(r, red_rd + 512 + ((j >> 1) * 8 + (j & 1)) * 16);
                l[j] = (r[0] + r[1]) + (r[2] + r[3]);
            }
            if (tid < 4) {
                st_async_v4(peer + kOffPeerStats + tid * 16, m, peer + kBarStats);
                st_async_v4(peer + kOffPeerStats + 64 + tid * 16, l, peer + kBarStats);
                st_async_v4(peer + kOffPeerStats + 128 + tid * 16, a, peer + kBarStats);
                st_async_v4(peer + kOffPeerStats + 192 + tid * 16, a_prev, peer + kBarStats);
            }
            mbar_wait_peer(sb + kBarStats);
            float pm[4], pl[4], pa[4], pa_prev[4], coef[6][4];
            lds128(pm, sb + kOffPeerStats + t4 * 16);
            lds128(pl, sb + kOffPeerStats + 64 + t4 * 16);
            lds128(pa, sb + kOffPeerStats + 128 + t4 * 16);
            lds128(pa_prev, sb + kOffPeerStats + 192 + t4 * 16);
#pragma unroll
            for (int j = 0; j < 4; j++) {
                const float mt = fmaxf(m[j], pm[j]);
                const float eo = ex2((m[j] - mt) * c), ep = ex2((pm[j] - mt) * c);
                const float inv = 1.f / (eo * l[j] + ep * pl[j]);
                coef[0][j] = eo * inv;
                coef[1][j] = ep * inv;
                coef[2][j] = coef[0][j] * a[j];
                coef[3][j] = coef[1][j] * pa[j];
                coef[4][j] = coef[2][j] * a_prev[j];
                coef[5][j] = coef[3][j] * pa_prev[j];
            }
            if (tid < 4) {
#pragma unroll
                for (int q = 0; q < 6; q++) sts128(sb + kOffCoef + q * 64 + tid * 16, coef[q]);
            }
            __syncwarp();
            if (lane == 0) mbar_arrive(sb + kBarEnd);
            mbar_wait(sb + kBarAck, 0);
        }
    } else {
        float o[2][8], T[2][2][8], alpha[2][4];
#pragma unroll
        for (int i = 0; i < 8; i++) o[0][i] = o[1][i] = 0.f;
        const int wt = tid - 128;
        const uint32_t dv0 = uniform(desc_base + rank * (1024 >> 4));
        const uint32_t dv1 = dv0 + (1024 >> 4) - rank * (2048 >> 4);
        const uint32_t dp = uniform((((sb + kOffP) & 0x3FFFF) >> 4) | ((128 >> 4) << 16));
        asm volatile("barrier.cluster.wait.aligned;" ::: "memory");

        RingPos vc{1, 1};
        int pb = 0;
#pragma unroll 1
        for (int t = 0; t < kTiles - kEnd; t++) {
            const uint32_t va = uniform(vc.slot * (kTileBytes >> 4)), pa = uniform(dp + pb * (kPStride >> 4));
            mbar_wait(sb + kBarFull + 8 * vc.pos, 0);
            lds128(alpha[0], sb + kOffP + pb * kPStride + kPBytes + t4 * 16);
            pin(T[0][0]); pin(T[0][1]);
            issue_pv(T[0], dv0 + va, dv1 + va, pa);
            wg_wait<0>();
            if (lane == 0) mbar_arrive(sb + kBarEmpty + 8 * vc.slot);
            fold(o[1], T[0][1], alpha[0]);
            fold(o[0], T[0][0], alpha[0]);
            vc.step(2);
            if (++pb == kEnd) pb = 0;
        }

#pragma unroll
        for (int j = 0; j < kEnd - kSplit; j++) {
            const int t = kTiles - kEnd + j, pos = kLoads - kEnd + j, slot = pos % kSlots;
            float (&d)[2][8] = T[j & 1];
            float (&prev)[2][8] = T[(j + 1) & 1];
            pin(d[0]); pin(d[1]);
            mbar_wait(sb + kBarFull + 8 * pos, 0);
            lds128(alpha[j & 1], sb + kOffP + (t % kEnd) * kPStride + kPBytes + t4 * 16);
            issue_pv(d, dv0 + slot * (kTileBytes >> 4), dv1 + slot * (kTileBytes >> 4), dp + (t % kEnd) * (kPStride >> 4));
            if (pos + kSlots < kLoads) {
                wg_wait<0>();
                if (lane == 0) mbar_arrive(sb + kBarEmpty + 8 * slot);
            }
            if (j > 0) {
                wg_wait<1>();
                fold(o[1], prev[1], alpha[(j + 1) & 1]);
                fold(o[0], prev[0], alpha[(j + 1) & 1]);
            }
            if (j == kEnd - kSplit - 1) {
                wg_wait<0>();
                fold(o[1], d[1], alpha[j & 1]);
                st_async_v4(peer + kOffPeerO + wt * 16, &o[1][0], peer + kBarEnd);
                st_async_v4(peer + kOffPeerO + 2048 + wt * 16, &o[1][4], peer + kBarEnd);
                fold(o[0], d[0], alpha[j & 1]);
            }
        }

        const uint32_t dh_own = uniform(desc_base + rank * (16384 >> 4));
        const uint32_t dh_peer = dh_own + (16384 >> 4) - rank * (32768 >> 4);
        float coef[6][4], r[8];
#pragma unroll
        for (int h = 0; h < 2 * kSplit; h++) {
            const int u = h >> 1;
            const uint32_t va = ((kWhole + u) % kSlots) * (kTileBytes >> 4);
            float (&d)[8] = T[u][h & 1];
            pin(d);
            if (h & 1) {
                mbar_wait(sb + kBarHalf + 8 * h, 0);
                issue_pv_half(d, dh_own + va, dp + ((kTiles - kSplit + u) % kEnd) * (kPStride >> 4));
            } else {
                mbar_wait_peer(sb + kBarHalf + 8 * h);
                issue_pv_half(d, dh_peer + va, dp - ((kOffP - kOffPeerP) >> 4) + u * (kPBytes >> 4));
            }
            if (h == 2 * kSplit - 2 && wt == 0)
                asm volatile("mbarrier.arrive.relaxed.cluster.shared::cluster.b64 _, [%0];" ::"r"(peer + kBarAck) : "memory");
            if (h == 1) {
                mbar_wait_peer(sb + kBarEnd);
#pragma unroll
                for (int q = 0; q < 6; q++) lds128(coef[q], sb + kOffCoef + q * 64 + t4 * 16);
                float px[8];
                lds128(&px[0], sb + kOffPeerO + wt * 16);
                lds128(&px[4], sb + kOffPeerO + 2048 + wt * 16);
#pragma unroll
                for (int i = 0; i < 8; i++) r[i] = fmaf(o[0][i], coef[4][col(i)], px[i] * coef[5][col(i)]);
            }
            if (h > 0) {
                float (&e)[8] = T[(h - 1) >> 1][(h - 1) & 1];
                wg_wait<1>();
                pin(e);
#pragma unroll
                for (int i = 0; i < 8; i++) r[i] = fmaf(e[i], coef[2 * kSplit - h][col(i)], r[i]);
            }
        }
        wg_wait<0>();
        pin(T[kSplit - 1][1]);
#pragma unroll
        for (int i = 0; i < 8; i++) r[i] = fmaf(T[kSplit - 1][1][i], coef[0][col(i)], r[i]);

        uint32_t* dst = reinterpret_cast<uint32_t*>(out + (head * kQRows + (lane >> 2)) * kD + rank * 64 + warp * 16 + 2 * t4);
#pragma unroll
        for (int b = 0; b < 4; b++) {
            uint32_t tr;
            asm volatile("movmatrix.sync.aligned.m8n8.trans.b16 %0, %1;" : "=r"(tr) : "r"(pack_bf16(r[2 * b], r[2 * b + 1])));
            dst[(b >> 1) * (8 * kD / 2) + (b & 1) * 4] = tr;
        }
    }
}

using EncodeFn = CUresult (*)(CUtensorMap*, CUtensorMapDataType, cuuint32_t, void*, const cuuint64_t*,
                              const cuuint64_t*, const cuuint32_t*, const cuuint32_t*, CUtensorMapInterleave,
                              CUtensorMapSwizzle, CUtensorMapL2promotion, CUtensorMapFloatOOBfill);

CUtensorMap make_map(EncodeFn encode, void* ptr, uint64_t rows, uint32_t box_halves, uint32_t box_rows) {
    CUtensorMap map;
    const cuuint64_t dims[4] = {64, 8, 2, rows / 8};
    const cuuint64_t strides[3] = {256, 128, 2048};
    const cuuint32_t box[4] = {64, 8, box_halves, box_rows / 8};
    const cuuint32_t elem[4] = {1, 1, 1, 1};
    encode(&map, CU_TENSOR_MAP_DATA_TYPE_BFLOAT16, 4, ptr, dims, strides, box, elem, CU_TENSOR_MAP_INTERLEAVE_NONE,
           CU_TENSOR_MAP_SWIZZLE_128B, CU_TENSOR_MAP_L2_PROMOTION_NONE, CU_TENSOR_MAP_FLOAT_OOB_FILL_NONE);
    return map;
}

}

extern "C" void kernel_launch(void* const* d_in, const int* in_sizes, int n_in, void* d_out, int out_size) {
    (void)in_sizes; (void)n_in; (void)out_size;
    static EncodeFn encode = nullptr;
    if (!encode) {
        cudaDriverEntryPointQueryResult status;
        cudaGetDriverEntryPoint("cuTensorMapEncodeTiled", reinterpret_cast<void**>(&encode), cudaEnableDefault, &status);
        cudaFuncSetAttribute(gqa_decode_kernel, cudaFuncAttributeMaxDynamicSharedMemorySize, kSmemBytes);
    }
    const uint64_t kv_rows = (uint64_t)kHeads * kSk;
    const CUtensorMap map_q = make_map(encode, d_in[0], (uint64_t)kHeads * kQRows, 2, kQRows);
    const CUtensorMap map_k = make_map(encode, d_in[1], kv_rows, 2, kTile);
    const CUtensorMap map_v = make_map(encode, d_in[2], kv_rows, 2, kTile);
    const CUtensorMap map_v_half = make_map(encode, d_in[2], kv_rows, 1, kTile);
    gqa_decode_kernel<<<kCtas, kThreads, kSmemBytes>>>(map_k, map_v, map_q, map_v_half,
                                                       static_cast<__nv_bfloat16*>(d_out),
                                                       static_cast<const char*>(d_in[1]));
}
```

```cpp
#include <cuda_runtime.h>
#include <cuda_bf16.h>
#include <cuda.h>
#include <stdint.h>

namespace {

constexpr int kD = 128;
constexpr int kSk = 8192;
constexpr int kHeads = 64;
constexpr int kQRows = 16;
constexpr int kTile = 128;
constexpr int kTiles = kSk / 2 / kTile;
constexpr int kLoads = 2 * kTiles;
constexpr int kSlots = 5;
constexpr int kEnd = 5;
constexpr int kPBufs = (kEnd + kSlots + 1) / 2;
constexpr int kWhole = kLoads - 1;
constexpr int kPairs = kWhole / 2;
constexpr int kGroups = kTile / 8;
constexpr int kThreads = 320;
constexpr int kCtas = 2 * kHeads;
constexpr int kPaceFrom = 8;
constexpr int kPaceSlack = 72;

constexpr uint32_t kTileBytes = kTile * kD * 2;
constexpr uint32_t kQBytes = kQRows * kD * 2;
constexpr uint32_t kPBytes = kTile * kQRows * 2;
constexpr uint32_t kPStride = kPBytes + 64;

constexpr uint32_t kOffRing = 0;
constexpr uint32_t kOffQ = kOffRing + kSlots * kTileBytes;
constexpr uint32_t kOffPeerO = kOffQ + kQBytes;
constexpr uint32_t kOffPeerP = kOffPeerO + 4096;
constexpr uint32_t kOffP = kOffPeerP + kPBytes;
constexpr uint32_t kOffPeerStats = kOffP + kPBufs * kPStride;
constexpr uint32_t kOffRed = kOffPeerStats + 192;
constexpr uint32_t kOffCoef = kOffRed + 768;
constexpr uint32_t kBarFull = kOffCoef + 256;
constexpr uint32_t kBarPeerKeys = kBarFull + 8 * kWhole;
constexpr uint32_t kBarOwnKeys = kBarPeerKeys + 8;
constexpr uint32_t kBarEmpty = kBarOwnKeys + 8;
constexpr uint32_t kBarEnd = kBarEmpty + 8 * kSlots;
constexpr uint32_t kBarStats = kBarEnd + 8;
constexpr uint32_t kBarAck = kBarStats + 8;
constexpr uint32_t kOffPace = kBarAck + 8;
constexpr uint32_t kSmemBytes = kOffPace + 8;

static_assert(kEnd >= 2 && kEnd <= kSlots, "no slot of the final V block is refilled");
static_assert(kPBufs >= kEnd && 2 * kPBufs >= kEnd + kSlots,
              "a P^T buffer is free once the K tile that refills it has landed");
static_assert(kPaceSlack >= kCtas / 2, "the slowest CTA is never held back");

constexpr uint64_t kEvictFirst = 0x12F0000000000000ull;
constexpr int kSpinLimit = 1 << 24;

constexpr uint32_t kHiTile = (2048 >> 4) | (1u << 30);
constexpr uint32_t kHiHalf = (1024 >> 4) | (1u << 30);
constexpr uint32_t kHiP = 256 >> 4;

__device__ unsigned g_pairs_issued;

__device__ __forceinline__ int step_group(int head, int t) { return head * (kSk / 8) + t * 2 * kGroups; }

__device__ __forceinline__ bool load_is_v(int i) { return i < kLoads - 2 * kEnd ? (i & 1) : i >= kLoads - kEnd; }

__device__ __forceinline__ void mbar_init(uint32_t bar, uint32_t count) {
    asm volatile("mbarrier.init.shared::cta.b64 [%0], %1;" ::"r"(bar), "r"(count) : "memory");
}
__device__ __forceinline__ void mbar_expect_tx(uint32_t bar, uint32_t bytes) {
    asm volatile("mbarrier.arrive.expect_tx.shared::cta.b64 _, [%0], %1;" ::"r"(bar), "r"(bytes) : "memory");
}
__device__ __forceinline__ void mbar_arrive(uint32_t bar) {
    asm volatile("mbarrier.arrive.shared::cta.b64 _, [%0];" ::"r"(bar) : "memory");
}
__device__ __forceinline__ void mbar_wait(uint32_t bar, uint32_t parity) {
    asm volatile(
        "{\n.reg .pred p;\n.reg .u32 n;\nmov.u32 n, 0;\n"
        "WAIT_LOOP:\n"
        "mbarrier.try_wait.parity.shared::cta.b64 p, [%0], %1;\n"
        "@p bra WAIT_DONE;\n"
        "add.u32 n, n, 1;\nsetp.lt.u32 p, n, %2;\n@p bra WAIT_LOOP;\ntrap;\n"
        "WAIT_DONE:\n}"
        ::"r"(bar), "r"(parity), "n"(kSpinLimit) : "memory");
}
__device__ __forceinline__ void mbar_wait_peer(uint32_t bar) {
    mbar_wait(bar, 0);
    asm volatile("fence.acquire.sync_restrict::shared::cluster.cluster;" ::: "memory");
}
__device__ __forceinline__ void tma_load(uint32_t dst, const CUtensorMap* map, int half, int group, uint32_t bar) {
    asm volatile(
        "cp.async.bulk.tensor.4d.shared::cluster.global.mbarrier::complete_tx::bytes.L2::cache_hint "
        "[%0], [%1, {%3, %3, %4, %5}], [%2], %6;"
        ::"r"(dst), "l"(map), "r"(bar), "r"(0), "r"(half), "r"(group), "l"(kEvictFirst) : "memory");
}
__device__ __forceinline__ void copy_to_peer(uint32_t dst, uint32_t src, uint32_t bytes, uint32_t bar) {
    asm volatile("cp.async.bulk.shared::cluster.shared::cta.mbarrier::complete_tx::bytes [%0], [%1], %2, [%3];"
                 ::"r"(dst), "r"(src), "r"(bytes), "r"(bar) : "memory");
}
__device__ __forceinline__ void st_async_v4(uint32_t dst, const float* v, uint32_t bar) {
    asm volatile("st.async.weak.shared::cluster.mbarrier::complete_tx::bytes.v4.f32 [%0], {%1, %2, %3, %4}, [%5];"
                 ::"r"(dst), "f"(v[0]), "f"(v[1]), "f"(v[2]), "f"(v[3]), "r"(bar) : "memory");
}
__device__ __forceinline__ void lds128(float* v, uint32_t addr) {
    asm volatile("ld.shared.v4.f32 {%0, %1, %2, %3}, [%4];"
                 : "=f"(v[0]), "=f"(v[1]), "=f"(v[2]), "=f"(v[3]) : "r"(addr) : "memory");
}
__device__ __forceinline__ void sts128(uint32_t addr, const float* v) {
    asm volatile("st.shared.v4.f32 [%0], {%1, %2, %3, %4};"
                 ::"r"(addr), "f"(v[0]), "f"(v[1]), "f"(v[2]), "f"(v[3]) : "memory");
}
__device__ __forceinline__ void sts32(uint32_t addr, float v) {
    asm volatile("st.shared.f32 [%0], %1;" ::"r"(addr), "f"(v) : "memory");
}
__device__ __forceinline__ void score_group_sync() { asm volatile("bar.sync 1, 128;" ::: "memory"); }
__device__ __forceinline__ float ex2(float x) {
    float y;
    asm("ex2.approx.ftz.f32 %0, %1;" : "=f"(y) : "f"(x));
    return y;
}
__device__ __forceinline__ uint32_t pack_bf16(float lo, float hi) {
    uint32_t r;
    asm("cvt.rn.bf16x2.f32 %0, %1, %2;" : "=r"(r) : "f"(hi), "f"(lo));
    return r;
}
__device__ __forceinline__ uint32_t uniform(uint32_t x) { return __shfl_sync(0xffffffffu, x, 0); }

__device__ __forceinline__ void wg_fence() { asm volatile("wgmma.fence.sync.aligned;" ::: "memory"); }
__device__ __forceinline__ void wg_commit() { asm volatile("wgmma.commit_group.sync.aligned;" ::: "memory"); }
template <int N>
__device__ __forceinline__ void wg_wait() { asm volatile("wgmma.wait_group.sync.aligned %0;" ::"n"(N) : "memory"); }

template <int kAccumulate, int kTransA, uint32_t kHiA, uint32_t kHiB>
__device__ __forceinline__ void wgmma(float (&d)[8], uint32_t lo_a, uint32_t lo_b) {
    asm volatile(
        "{\n.reg .b64 da, db;\nmov.b64 da, {%8, %12};\nmov.b64 db, {%9, %13};\n"
        "wgmma.mma_async.sync.aligned.m64n16k16.f32.bf16.bf16 "
        "{%0, %1, %2, %3, %4, %5, %6, %7}, da, db, %10, 1, 1, %11, 0;\n}"
        : "+f"(d[0]), "+f"(d[1]), "+f"(d[2]), "+f"(d[3]), "+f"(d[4]), "+f"(d[5]), "+f"(d[6]), "+f"(d[7])
        : "r"(lo_a), "r"(lo_b), "n"(kAccumulate), "n"(kTransA), "n"(kHiA), "n"(kHiB));
}
__device__ __forceinline__ void pin(float (&d)[8]) {
    asm volatile("" : "+f"(d[0]), "+f"(d[1]), "+f"(d[2]), "+f"(d[3]), "+f"(d[4]), "+f"(d[5]), "+f"(d[6]), "+f"(d[7])::"memory");
}

__device__ __forceinline__ void issue_pv(float (&d)[2][8], uint32_t a0, uint32_t a1, uint32_t p) {
    wg_fence();
    wgmma<0, 1, kHiTile, kHiP>(d[1], a1, p);
    wgmma<0, 1, kHiTile, kHiP>(d[0], a0, p);
#pragma unroll
    for (int k = 1; k < kTile / 16; k++) {
        wgmma<1, 1, kHiTile, kHiP>(d[1], a1 + k * (4096 >> 4), p + k * (512 >> 4));
        wgmma<1, 1, kHiTile, kHiP>(d[0], a0 + k * (4096 >> 4), p + k * (512 >> 4));
    }
    wg_commit();
}
__device__ __forceinline__ void issue_pv_half(float (&d)[8], uint32_t a, uint32_t p) {
    wg_fence();
    wgmma<0, 1, kHiHalf, kHiP>(d, a, p);
#pragma unroll
    for (int k = 1; k < kTile / 16; k++) wgmma<1, 1, kHiHalf, kHiP>(d, a + k * (2048 >> 4), p + k * (512 >> 4));
    wg_commit();
}

__device__ __forceinline__ constexpr int col(int i) { return (i >> 2) * 2 + (i & 1); }

__device__ __forceinline__ void fold(float (&acc)[8], float (&d)[8], const float (&a)[4]) {
    pin(d);
#pragma unroll
    for (int i = 0; i < 8; i++) acc[i] = fmaf(acc[i], a[col(i)], d[i]);
}

template <bool kMax>
__device__ __forceinline__ float warp_col_reduce(const float (&x)[4], int lane) {
    const bool b2 = lane & 4, b3 = lane & 8;
    float a = b2 ? x[2] : x[0], b = b2 ? x[3] : x[1];
    const float ra = __shfl_xor_sync(0xffffffffu, b2 ? x[0] : x[2], 4);
    const float rb = __shfl_xor_sync(0xffffffffu, b2 ? x[1] : x[3], 4);
    a = kMax ? fmaxf(a, ra) : a + ra;
    b = kMax ? fmaxf(b, rb) : b + rb;
    float keep = b3 ? b : a;
    const float r2 = __shfl_xor_sync(0xffffffffu, b3 ? a : b, 8);
    keep = kMax ? fmaxf(keep, r2) : keep + r2;
    const float r3 = __shfl_xor_sync(0xffffffffu, keep, 16);
    return kMax ? fmaxf(keep, r3) : keep + r3;
}

__device__ __forceinline__ void count_pair() {
    asm volatile("red.relaxed.gpu.global.inc.u32 [%0], %1;" ::"l"(&g_pairs_issued), "n"(kPairs * kCtas - 1) : "memory");
}
__device__ __forceinline__ bool pace(uint32_t progress, int i) {
    for (int it = 0; it < 1024; it++) {
        int pairs;
        asm volatile("ld.volatile.shared.u32 %0, [%1];" : "=r"(pairs) : "r"(progress) : "memory");
        if (pairs >= i * (kCtas / 2) - kPaceSlack) return true;
    }
    return false;
}

struct RingPos {
    int pos, slot;
    __device__ __forceinline__ void step(int n) {
        pos += n;
        slot += n;
        if (slot >= kSlots) slot -= kSlots;
    }
};

__global__ void __cluster_dims__(2, 1, 1) __launch_bounds__(kThreads, 1)
gqa_decode_kernel(const __grid_constant__ CUtensorMap map_k, const __grid_constant__ CUtensorMap map_v,
                  const __grid_constant__ CUtensorMap map_q, const __grid_constant__ CUtensorMap map_v_half,
                  __nv_bfloat16* __restrict__ out, const char* __restrict__ k_bytes) {
    const int tid = threadIdx.x;
    const int head = blockIdx.x >> 1;
    const int rank = blockIdx.x & 1;

    asm volatile("prefetch.global.L2 [%0];"
                 ::"l"(k_bytes + (size_t)(step_group(head, 0) + rank * kGroups) * 2048 + (tid & 255) * 128) : "memory");

    extern __shared__ __align__(1024) uint8_t smem[];
    const uint32_t sb = (uint32_t)__cvta_generic_to_shared(smem);

    if (tid == 256) {
#pragma unroll
        for (int i = 0; i < kSlots; i++) {
            const uint32_t bar = sb + kBarFull + 8 * i;
            mbar_init(bar, (i & 1) ? 5 : 1);
            mbar_expect_tx(bar, kTileBytes + (i == 0 ? kQBytes : 0));
            tma_load(sb + kOffRing + i * kTileBytes, (i & 1) ? &map_v : &map_k, 0,
                     step_group(head, i >> 1) + rank * kGroups, bar);
            if (i == 0) tma_load(sb + kOffQ, &map_q, 0, head * (kQRows / 8), bar);
        }
    } else if ((tid & 3) == 0 && (tid >> 2) >= kSlots && (tid >> 2) < kWhole) {
        const uint32_t bar = sb + kBarFull + 8 * (tid >> 2);
        mbar_init(bar, load_is_v(tid >> 2) ? 5 : 1);
        mbar_expect_tx(bar, kTileBytes);
    } else if (tid == 1) {
        if (sb & 1023) __trap();
#pragma unroll
        for (int i = 0; i < kSlots; i++) mbar_init(sb + kBarEmpty + 8 * i, 4);
        mbar_init(sb + kBarPeerKeys, 1);
        mbar_init(sb + kBarOwnKeys, 5);
        mbar_expect_tx(sb + kBarPeerKeys, kTileBytes / 2 + kPBytes);
        mbar_expect_tx(sb + kBarOwnKeys, kTileBytes / 2);
        asm volatile("st.shared.v2.u32 [%0], {%1, %1};" ::"r"(sb + kOffPace), "r"(0) : "memory");
        mbar_init(sb + kBarEnd, 2);
        mbar_init(sb + kBarStats, 1);
        mbar_init(sb + kBarAck, 1);
        mbar_expect_tx(sb + kBarStats, 192);
        mbar_expect_tx(sb + kBarEnd, 4096);
        asm volatile("fence.mbarrier_init.release.cluster;" ::: "memory");
    }
    __syncthreads();
    asm volatile("barrier.cluster.arrive.relaxed.aligned;" ::: "memory");

    const int lane = tid & 31, warp = (tid >> 5) & 3, t4 = lane & 3;
    const float c = 0.08838834764831845f * 1.4426950408889634f;
    const uint32_t desc_base = ((sb & 0x3FFFF) >> 4) | (1u << 16);
    uint32_t peer;
    asm("mapa.shared::cluster.u32 %0, %1, %2;" : "=r"(peer) : "r"(sb), "r"(rank ^ 1));

    if (tid >= 256) {
        if (tid == 256) {
            int slot = 0;
            uint32_t parity = 0;
            bool paced = true;
#pragma unroll
            for (int i = 0; i < kSlots / 2; i++) count_pair();
#pragma unroll 1
            for (int i = kSlots; i < kWhole; i++) {
                const bool is_v = load_is_v(i);
                const int tile = i < kLoads - 2 * kEnd ? (i >> 1) : (is_v ? i - kTiles : i - (kTiles - kEnd));
                mbar_wait(sb + kBarEmpty + 8 * slot, parity);
                if (paced && i >= kPaceFrom && i < 2 * kPairs) paced = pace(sb + kOffPace, i);
                tma_load(sb + kOffRing + slot * kTileBytes, is_v ? &map_v : &map_k, 0,
                         step_group(head, tile) + rank * kGroups, sb + kBarFull + 8 * i);
                if (i & 1) count_pair();
                if (++slot == kSlots) { slot = 0; parity ^= 1; }
            }
            asm volatile("st.volatile.shared.u32 [%0], %1;" ::"r"(sb + kOffPace + 4), "r"(1) : "memory");
            mbar_wait(sb + kBarEmpty + 8 * slot, parity);
            mbar_wait(sb + kBarFull + 8 * (kWhole - 1), 0);
#pragma unroll
            for (int h = 0; h < 2; h++) {
                const int keys = rank ^ 1 ^ h;
                tma_load(sb + kOffRing + slot * kTileBytes + keys * (kTileBytes / 2), &map_v_half, rank,
                         step_group(head, kTiles - 1) + keys * kGroups, sb + kBarPeerKeys + 8 * h);
            }
        } else if (tid == 288) {
            for (int it = 0; it < 4096; it++) {
                uint32_t pairs, done;
                asm volatile("ld.relaxed.gpu.global.u32 %0, [%1];" : "=r"(pairs) : "l"(&g_pairs_issued) : "memory");
                asm volatile("st.volatile.shared.u32 [%0], %1;" ::"r"(sb + kOffPace), "r"(pairs) : "memory");
                asm volatile("ld.volatile.shared.u32 %0, [%1];" : "=r"(done) : "r"(sb + kOffPace + 4) : "memory");
                if (done) break;
            }
        }
    } else if (tid < 128) {
        const int my_col = 2 * t4 + ((lane >> 3) & 1) + 8 * ((lane >> 2) & 1);
        const uint32_t red_wr = sb + kOffRed + (my_col * 4 + warp) * 4;
        const uint32_t red_rd = sb + kOffRed + (2 * t4) * 16;
        const uint32_t dq = uniform(desc_base + (kOffQ >> 4));
        float s[2][8], m[4], l[4], a[4];
#pragma unroll
        for (int j = 0; j < 4; j++) { m[j] = -INFINITY; l[j] = 0.f; }
        RingPos kc{0, 0};
        int pb = 0;
        asm volatile("barrier.cluster.wait.aligned;" ::: "memory");

#pragma unroll 1
        for (int t = 0; t < kTiles; t++) {
            const uint32_t dk = uniform(desc_base + kc.slot * (kTileBytes >> 4));
            mbar_wait(sb + kBarFull + 8 * kc.pos, 0);
            pin(s[0]); pin(s[1]);
            wg_fence();
#pragma unroll
            for (int k = 0; k < kD / 16; k++) {
                const uint32_t off = ((k >> 2) * 1024 + (k & 3) * 32) >> 4;
#pragma unroll
                for (int mt = 0; mt < 2; mt++) {
                    if (k == 0) wgmma<0, 0, kHiTile, kHiTile>(s[mt], dk + off + mt * (16384 >> 4), dq + off);
                    else        wgmma<1, 0, kHiTile, kHiTile>(s[mt], dk + off + mt * (16384 >> 4), dq + off);
                }
            }
            wg_commit();
            wg_wait<0>();
            pin(s[0]); pin(s[1]);
            if (lane == 0) mbar_arrive(sb + kBarEmpty + 8 * kc.slot);
            kc.step(t < kTiles - kEnd ? 2 : 1);

            float x[4];
#pragma unroll
            for (int j = 0; j < 4; j++) {
                const int i0 = (j >> 1) * 4 + (j & 1);
                x[j] = fmaxf(fmaxf(s[0][i0], s[0][i0 + 2]), fmaxf(s[1][i0], s[1][i0 + 2]));
            }
            const float wmax = warp_col_reduce<true>(x, lane);
            const uint32_t rb = (t & 1) * 256;
            if (lane < 16) sts32(red_wr + rb, wmax);
            score_group_sync();
            float mc[4];
#pragma unroll
            for (int j = 0; j < 4; j++) {
                float r[4];
                lds128(r, red_rd + rb + ((j >> 1) * 8 + (j & 1)) * 16);
                const float mn = fmaxf(fmaxf(fmaxf(r[0], r[1]), fmaxf(r[2], r[3])), m[j]);
                a[j] = ex2((m[j] - mn) * c);
                m[j] = mn;
                mc[j] = mn * c;
                l[j] *= a[j];
            }
            const uint32_t p_buf = sb + kOffP + pb * kPStride;
#pragma unroll
            for (int mt = 0; mt < 2; mt++) {
                float p[8];
#pragma unroll
                for (int i = 0; i < 8; i++) {
                    p[i] = ex2(fmaf(s[mt][i], c, -mc[col(i)]));
                    l[col(i)] += p[i];
                }
                asm volatile("stmatrix.sync.aligned.m8n8.x4.trans.shared.b16 [%0], {%1, %2, %3, %4};"
                             ::"r"(p_buf + mt * 2048 + warp * 512 + lane * 16), "r"(pack_bf16(p[0], p[1])),
                               "r"(pack_bf16(p[2], p[3])), "r"(pack_bf16(p[4], p[5])), "r"(pack_bf16(p[6], p[7]))
                             : "memory");
            }
            if (tid < 4) sts128(p_buf + kPBytes + tid * 16, a);
            asm volatile("fence.proxy.async.shared::cta;" ::: "memory");
            __syncwarp();
            if (lane == 0) {
                if (t < kTiles - 1) {
                    mbar_arrive(sb + kBarFull + 8 * (t < kTiles - kEnd ? 2 * t + 1 : t + kTiles));
                } else {
                    mbar_arrive(sb + kBarOwnKeys);
                    copy_to_peer(peer + kOffPeerP + warp * 512, p_buf + warp * 512, 512, peer + kBarPeerKeys);
                    copy_to_peer(peer + kOffPeerP + warp * 512 + 2048, p_buf + warp * 512 + 2048, 512, peer + kBarPeerKeys);
                }
            }
            if (++pb == kPBufs) pb = 0;
        }

        const float wsum = warp_col_reduce<false>(l, lane);
        if (lane < 16) sts32(red_wr + 512, wsum);
        score_group_sync();
        if (warp == 0) {
#pragma unroll
            for (int j = 0; j < 4; j++) {
                float r[4];
                lds128(r, red_rd + 512 + ((j >> 1) * 8 + (j & 1)) * 16);
                l[j] = (r[0] + r[1]) + (r[2] + r[3]);
            }
            if (tid < 4) {
                st_async_v4(peer + kOffPeerStats + tid * 16, m, peer + kBarStats);
                st_async_v4(peer + kOffPeerStats + 64 + tid * 16, l, peer + kBarStats);
                st_async_v4(peer + kOffPeerStats + 128 + tid * 16, a, peer + kBarStats);
            }
            mbar_wait_peer(sb + kBarStats);
            float pm[4], pl[4], pa[4], coef[4][4];
            lds128(pm, sb + kOffPeerStats + t4 * 16);
            lds128(pl, sb + kOffPeerStats + 64 + t4 * 16);
            lds128(pa, sb + kOffPeerStats + 128 + t4 * 16);
#pragma unroll
            for (int j = 0; j < 4; j++) {
                const float mt = fmaxf(m[j], pm[j]);
                const float eo = ex2((m[j] - mt) * c), ep = ex2((pm[j] - mt) * c);
                const float inv = 1.f / (eo * l[j] + ep * pl[j]);
                coef[0][j] = eo * inv;
                coef[1][j] = ep * inv;
                coef[2][j] = coef[0][j] * a[j];
                coef[3][j] = coef[1][j] * pa[j];
            }
            if (tid < 4) {
#pragma unroll
                for (int q = 0; q < 4; q++) sts128(sb + kOffCoef + q * 64 + tid * 16, coef[q]);
            }
            __syncwarp();
            if (lane == 0) mbar_arrive(sb + kBarEnd);
            mbar_wait(sb + kBarAck, 0);
        }
    } else {
        float o[2][8], T[2][2][8], alpha[2][4];
#pragma unroll
        for (int i = 0; i < 8; i++) o[0][i] = o[1][i] = 0.f;
        const int wt = tid - 128;
        const uint32_t dv0 = uniform(desc_base + rank * (1024 >> 4));
        const uint32_t dv1 = dv0 + (1024 >> 4) - rank * (2048 >> 4);
        const uint32_t dp = uniform((((sb + kOffP) & 0x3FFFF) >> 4) | ((128 >> 4) << 16));
        asm volatile("barrier.cluster.wait.aligned;" ::: "memory");

        RingPos vc{1, 1};
        int pb = 0;
#pragma unroll 1
        for (int t = 0; t < kTiles - kEnd; t++) {
            const uint32_t va = uniform(vc.slot * (kTileBytes >> 4)), pa = uniform(dp + pb * (kPStride >> 4));
            mbar_wait(sb + kBarFull + 8 * vc.pos, 0);
            lds128(alpha[0], sb + kOffP + pb * kPStride + kPBytes + t4 * 16);
            pin(T[0][0]); pin(T[0][1]);
            issue_pv(T[0], dv0 + va, dv1 + va, pa);
            wg_wait<0>();
            __syncwarp();
            if (lane == 0) mbar_arrive(sb + kBarEmpty + 8 * vc.slot);
            fold(o[1], T[0][1], alpha[0]);
            fold(o[0], T[0][0], alpha[0]);
            vc.step(2);
            if (++pb == kPBufs) pb = 0;
        }

#pragma unroll
        for (int j = 0; j < kEnd - 1; j++) {
            const int t = kTiles - kEnd + j, pos = kLoads - kEnd + j, slot = pos % kSlots;
            float (&d)[2][8] = T[j & 1];
            float (&prev)[2][8] = T[(j + 1) & 1];
            pin(d[0]); pin(d[1]);
            mbar_wait(sb + kBarFull + 8 * pos, 0);
            lds128(alpha[j & 1], sb + kOffP + (t % kPBufs) * kPStride + kPBytes + t4 * 16);
            issue_pv(d, dv0 + slot * (kTileBytes >> 4), dv1 + slot * (kTileBytes >> 4), dp + (t % kPBufs) * (kPStride >> 4));
            if (j > 0) {
                wg_wait<1>();
                fold(o[1], prev[1], alpha[(j + 1) & 1]);
                fold(o[0], prev[0], alpha[(j + 1) & 1]);
            }
            if (j == kEnd - 2) {
                wg_wait<0>();
                fold(o[1], d[1], alpha[j & 1]);
                st_async_v4(peer + kOffPeerO + wt * 16, &o[1][0], peer + kBarEnd);
                st_async_v4(peer + kOffPeerO + 2048 + wt * 16, &o[1][4], peer + kBarEnd);
                fold(o[0], d[0], alpha[j & 1]);
            }
        }

        float coef[4][4], px[8], r[8];
        mbar_wait_peer(sb + kBarEnd);
#pragma unroll
        for (int q = 0; q < 4; q++) lds128(coef[q], sb + kOffCoef + q * 64 + t4 * 16);
        lds128(&px[0], sb + kOffPeerO + wt * 16);
        lds128(&px[4], sb + kOffPeerO + 2048 + wt * 16);
#pragma unroll
        for (int i = 0; i < 8; i++) r[i] = fmaf(o[0][i], coef[2][col(i)], px[i] * coef[3][col(i)]);

        const uint32_t dh = desc_base + (kWhole % kSlots) * (kTileBytes >> 4);
        const uint32_t dh_own = uniform(dh + rank * (16384 >> 4)), dh_peer = uniform(dh + (rank ^ 1) * (16384 >> 4));
        pin(T[0][0]); pin(T[0][1]);
        mbar_wait_peer(sb + kBarPeerKeys);
        issue_pv_half(T[0][1], dh_peer, dp - ((kOffP - kOffPeerP) >> 4));
        if (wt == 0)
            asm volatile("mbarrier.arrive.relaxed.cluster.shared::cluster.b64 _, [%0];" ::"r"(peer + kBarAck) : "memory");
        mbar_wait(sb + kBarOwnKeys, 0);
        issue_pv_half(T[0][0], dh_own, dp + ((kTiles - 1) % kPBufs) * (kPStride >> 4));
        wg_wait<1>();
        pin(T[0][1]);
#pragma unroll
        for (int i = 0; i < 8; i++) r[i] = fmaf(T[0][1][i], coef[1][col(i)], r[i]);
        wg_wait<0>();
        pin(T[0][0]);
#pragma unroll
        for (int i = 0; i < 8; i++) r[i] = fmaf(T[0][0][i], coef[0][col(i)], r[i]);

        uint32_t* dst = reinterpret_cast<uint32_t*>(out + (head * kQRows + (lane >> 2)) * kD + rank * 64 + warp * 16 + 2 * t4);
#pragma unroll
        for (int b = 0; b < 4; b++) {
            uint32_t tr;
            asm volatile("movmatrix.sync.aligned.m8n8.trans.b16 %0, %1;" : "=r"(tr) : "r"(pack_bf16(r[2 * b], r[2 * b + 1])));
            dst[(b >> 1) * (8 * kD / 2) + (b & 1) * 4] = tr;
        }
    }
}

using EncodeFn = CUresult (*)(CUtensorMap*, CUtensorMapDataType, cuuint32_t, void*, const cuuint64_t*,
                              const cuuint64_t*, const cuuint32_t*, const cuuint32_t*, CUtensorMapInterleave,
                              CUtensorMapSwizzle, CUtensorMapL2promotion, CUtensorMapFloatOOBfill);

CUtensorMap make_map(EncodeFn encode, void* ptr, uint64_t rows, uint32_t box_halves, uint32_t box_rows) {
    CUtensorMap map;
    const cuuint64_t dims[4] = {64, 8, 2, rows / 8};
    const cuuint64_t strides[3] = {256, 128, 2048};
    const cuuint32_t box[4] = {64, 8, box_halves, box_rows / 8};
    const cuuint32_t elem[4] = {1, 1, 1, 1};
    encode(&map, CU_TENSOR_MAP_DATA_TYPE_BFLOAT16, 4, ptr, dims, strides, box, elem, CU_TENSOR_MAP_INTERLEAVE_NONE,
           CU_TENSOR_MAP_SWIZZLE_128B, CU_TENSOR_MAP_L2_PROMOTION_NONE, CU_TENSOR_MAP_FLOAT_OOB_FILL_NONE);
    return map;
}

}

extern "C" void kernel_launch(void* const* d_in, const int* in_sizes, int n_in, void* d_out, int out_size) {
    (void)in_sizes; (void)n_in; (void)out_size;
    static EncodeFn encode = nullptr;
    if (!encode) {
        cudaDriverEntryPointQueryResult status;
        cudaGetDriverEntryPoint("cuTensorMapEncodeTiled", reinterpret_cast<void**>(&encode), cudaEnableDefault, &status);
        cudaFuncSetAttribute(gqa_decode_kernel, cudaFuncAttributeMaxDynamicSharedMemorySize, kSmemBytes);
    }
    const uint64_t kv_rows = (uint64_t)kHeads * kSk;
    const CUtensorMap map_q = make_map(encode, d_in[0], (uint64_t)kHeads * kQRows, 2, kQRows);
    const CUtensorMap map_k = make_map(encode, d_in[1], kv_rows, 2, kTile);
    const CUtensorMap map_v = make_map(encode, d_in[2], kv_rows, 2, kTile);
    const CUtensorMap map_v_half = make_map(encode, d_in[2], kv_rows, 1, kTile);
    gqa_decode_kernel<<<kCtas, kThreads, kSmemBytes>>>(map_k, map_v, map_q, map_v_half,
                                                       static_cast<__nv_bfloat16*>(d_out),
                                                       static_cast<const char*>(d_in[1]));
}
```
